```python
import torch

def _softmax(x, axis=-1):
    return torch.softmax(x, dim=axis)
def _gelu(x):
    return torch.nn.functional.gelu(x, approximate="tanh")
def _silu(x):
    return torch.nn.functional.silu(x)
def _sigmoid(x):
    return torch.sigmoid(x)
def _layernorm(x, axis=-1, eps=1e-5):
    m = x.mean(dim=axis, keepdim=True)
    v = x.var(dim=axis, keepdim=True, unbiased=False)
    return (x - m) / torch.sqrt(v + eps)
def _scatter_add(tgt, idx, src, axis=0):
    return tgt.clone().index_add_(axis, idx, src)
def _segment_sum(src, seg, n):
    out = torch.zeros((n,) + src.shape[1:], dtype=src.dtype)
    return out.index_add_(0, seg, src)
def _pad(x, pw):
    flat = tuple(v for pair in reversed(pw) for v in pair)
    return torch.nn.functional.pad(x, flat)

kernel_name = 'parallel_sum__sliding_local_dilated__glu_gated_reglu__prompt'

def setup_inputs():

    _w = (lambda a: (lambda t: t.to(torch.bfloat16) if t.is_floating_point() else t)(torch.as_tensor(a)))
    def _A_setup():
        B, S, D = 1, 2048, 576
        return {
            "x": _w((lambda *s: torch.randn(*s, dtype=torch.bfloat16) * 0.05)(B, S, D)),
            "wqkv": _w((lambda *s: torch.randn(*s, dtype=torch.bfloat16) * 0.05)(D, 3 * D)),
            "wo": _w((lambda *s: torch.randn(*s, dtype=torch.bfloat16) * 0.05)(D, D)),
        }
    _A_in = _A_setup()

    def _B_setup():
        B, S, D, F = 1, 2048, 576, 4608
        return {
            "x": _w((lambda *s: torch.randn(*s, dtype=torch.bfloat16) * 0.05)(B, S, D)),
            "W_gate": _w((lambda *s: torch.randn(*s, dtype=torch.bfloat16) * 0.8)(D, F) * (2.0 / D) ** 0.5),
            "W_up": _w((lambda *s: torch.randn(*s, dtype=torch.bfloat16) * 0.8)(D, F) * (2.0 / D) ** 0.5),
            "W_down": _w((lambda *s: torch.randn(*s, dtype=torch.bfloat16) * 0.8)(F, D) * (1.0 / F) ** 0.5),
        }
    _B_in = _B_setup()

    return {
        "A_x": _A_in["x"],
        "A_wqkv": _A_in["wqkv"],
        "A_wo": _A_in["wo"],
        "B_x": _B_in["x"],
        "B_W_gate": _B_in["W_gate"],
        "B_W_up": _B_in["W_up"],
        "B_W_down": _B_in["W_down"],
    }

def reference(A_x, A_wqkv, A_wo, B_x, B_W_gate, B_W_up, B_W_down):
    def _A_ref(x, wqkv, wo):
        B, S, D = x.shape
        H = 32; Dh = D // H
        W, dil = 8, 2
        qkv = (lambda x, *d: x.permute(*d))((x @ wqkv).reshape(B, S, 3, H, Dh), 2, 0, 3, 1, 4)
        q, k, v = qkv[0], qkv[1], qkv[2]
        scale = Dh ** -0.5
        pos = torch.arange(S)
        off = torch.arange(W) * dil
        idx = pos[:, None] - off[None, :]
        mask = idx >= 0
        idx_c = torch.where(mask, idx, 0).reshape(-1)
        kg = k[:, :, idx_c, :].reshape(B, H, S, W, Dh)
        vg = v[:, :, idx_c, :].reshape(B, H, S, W, Dh)
        logits = torch.einsum("bhsd,bhswd->bhsw", q, kg) * scale
        logits = torch.where(mask[None, None, :, :], logits, -1e9)
        attn = _softmax(logits, axis=-1)
        o = torch.einsum("bhsw,bhswd->bhsd", attn, vg)
        return (lambda x, *d: x.permute(*d))(o, 0, 2, 1, 3).reshape(B, S, D) @ wo

    def _B_ref(x, W_gate, W_up, W_down):
        gate = torch.einsum("bsd,df->bsf", x, W_gate)
        up = torch.einsum("bsd,df->bsf", x, W_up)
        gate = gate * (lambda x, dt: x.to(dt))(gate > 0, gate.dtype)
        h = gate * up
        return torch.einsum("bsf,fd->bsd", h, W_down)

    x = A_x
    xn = _layernorm(x, axis=-1)
    return x + _A_ref(xn, A_wqkv, A_wo) + _B_ref(xn, B_W_gate, B_W_up, B_W_down)
```

```cpp
#include <cuda_runtime.h>
#include <cuda_bf16.h>
#include <cuda.h>
#include <stdint.h>

constexpr int S_ = 2048, D_ = 576, F_ = 4608, QKV_ = 1728, ACT_ = 5184;
constexpr int NS1 = 5;
constexpr int NS2 = 4;
constexpr int XN_BYTES = 9 * 16384;
constexpr int RING1_OFF = XN_BYTES;
constexpr int ST1_BYTES = 16384;
constexpr int ST2_BYTES = 57344;
constexpr int DATA_BYTES = 229376;
constexpr int SMEM_BYTES = DATA_BYTES + 1024 + 256;
constexpr int NAGENTS = 128 * 6;

__device__ __align__(1024) __nv_bfloat16 g_qkv[S_ * QKV_];
__device__ __align__(1024) __nv_bfloat16 g_act[S_ * ACT_];
__device__ __align__(1024) float g_part[4 * S_ * D_];
__device__ unsigned int g_flags[192];
#define FAIL(code) __trap()
#define SPIN_MAX (1u << 24)

__device__ __forceinline__ void wgmma_n64(float (&d)[32], uint64_t da, uint64_t db, int scale_d) {
  asm volatile("{\n.reg .pred p;\nsetp.ne.b32 p, %34, 0;\n"
    "wgmma.mma_async.sync.aligned.m64n64k16.f32.bf16.bf16 {%0, %1, %2, %3, %4, %5, %6, %7, %8, %9, %10, %11, %12, %13, %14, %15, %16, %17, %18, %19, %20, %21, %22, %23, %24, %25, %26, %27, %28, %29, %30, %31}, %32, %33, p, 1, 1, 0, 1;\n}\n"
    : "+f"(d[0]), "+f"(d[1]), "+f"(d[2]), "+f"(d[3]), "+f"(d[4]), "+f"(d[5]), "+f"(d[6]), "+f"(d[7]), "+f"(d[8]), "+f"(d[9]), "+f"(d[10]), "+f"(d[11]), "+f"(d[12]), "+f"(d[13]), "+f"(d[14]), "+f"(d[15]), "+f"(d[16]), "+f"(d[17]), "+f"(d[18]), "+f"(d[19]), "+f"(d[20]), "+f"(d[21]), "+f"(d[22]), "+f"(d[23]), "+f"(d[24]), "+f"(d[25]), "+f"(d[26]), "+f"(d[27]), "+f"(d[28]), "+f"(d[29]), "+f"(d[30]), "+f"(d[31])
    : "l"(da), "l"(db), "r"(scale_d));
}

__device__ __forceinline__ void wgmma_n128(float (&d)[64], uint64_t da, uint64_t db, int scale_d) {
  asm volatile("{\n.reg .pred p;\nsetp.ne.b32 p, %66, 0;\n"
    "wgmma.mma_async.sync.aligned.m64n128k16.f32.bf16.bf16 {%0, %1, %2, %3, %4, %5, %6, %7, %8, %9, %10, %11, %12, %13, %14, %15, %16, %17, %18, %19, %20, %21, %22, %23, %24, %25, %26, %27, %28, %29, %30, %31, %32, %33, %34, %35, %36, %37, %38, %39, %40, %41, %42, %43, %44, %45, %46, %47, %48, %49, %50, %51, %52, %53, %54, %55, %56, %57, %58, %59, %60, %61, %62, %63}, %64, %65, p, 1, 1, 0, 1;\n}\n"
    : "+f"(d[0]), "+f"(d[1]), "+f"(d[2]), "+f"(d[3]), "+f"(d[4]), "+f"(d[5]), "+f"(d[6]), "+f"(d[7]), "+f"(d[8]), "+f"(d[9]), "+f"(d[10]), "+f"(d[11]), "+f"(d[12]), "+f"(d[13]), "+f"(d[14]), "+f"(d[15]), "+f"(d[16]), "+f"(d[17]), "+f"(d[18]), "+f"(d[19]), "+f"(d[20]), "+f"(d[21]), "+f"(d[22]), "+f"(d[23]), "+f"(d[24]), "+f"(d[25]), "+f"(d[26]), "+f"(d[27]), "+f"(d[28]), "+f"(d[29]), "+f"(d[30]), "+f"(d[31]), "+f"(d[32]), "+f"(d[33]), "+f"(d[34]), "+f"(d[35]), "+f"(d[36]), "+f"(d[37]), "+f"(d[38]), "+f"(d[39]), "+f"(d[40]), "+f"(d[41]), "+f"(d[42]), "+f"(d[43]), "+f"(d[44]), "+f"(d[45]), "+f"(d[46]), "+f"(d[47]), "+f"(d[48]), "+f"(d[49]), "+f"(d[50]), "+f"(d[51]), "+f"(d[52]), "+f"(d[53]), "+f"(d[54]), "+f"(d[55]), "+f"(d[56]), "+f"(d[57]), "+f"(d[58]), "+f"(d[59]), "+f"(d[60]), "+f"(d[61]), "+f"(d[62]), "+f"(d[63])
    : "l"(da), "l"(db), "r"(scale_d));
}

__device__ __forceinline__ void wgmma_n192(float (&d)[96], uint64_t da, uint64_t db, int scale_d) {
  asm volatile("{\n.reg .pred p;\nsetp.ne.b32 p, %98, 0;\n"
    "wgmma.mma_async.sync.aligned.m64n192k16.f32.bf16.bf16 {%0, %1, %2, %3, %4, %5, %6, %7, %8, %9, %10, %11, %12, %13, %14, %15, %16, %17, %18, %19, %20, %21, %22, %23, %24, %25, %26, %27, %28, %29, %30, %31, %32, %33, %34, %35, %36, %37, %38, %39, %40, %41, %42, %43, %44, %45, %46, %47, %48, %49, %50, %51, %52, %53, %54, %55, %56, %57, %58, %59, %60, %61, %62, %63, %64, %65, %66, %67, %68, %69, %70, %71, %72, %73, %74, %75, %76, %77, %78, %79, %80, %81, %82, %83, %84, %85, %86, %87, %88, %89, %90, %91, %92, %93, %94, %95}, %96, %97, p, 1, 1, 0, 1;\n}\n"
    : "+f"(d[0]), "+f"(d[1]), "+f"(d[2]), "+f"(d[3]), "+f"(d[4]), "+f"(d[5]), "+f"(d[6]), "+f"(d[7]), "+f"(d[8]), "+f"(d[9]), "+f"(d[10]), "+f"(d[11]), "+f"(d[12]), "+f"(d[13]), "+f"(d[14]), "+f"(d[15]), "+f"(d[16]), "+f"(d[17]), "+f"(d[18]), "+f"(d[19]), "+f"(d[20]), "+f"(d[21]), "+f"(d[22]), "+f"(d[23]), "+f"(d[24]), "+f"(d[25]), "+f"(d[26]), "+f"(d[27]), "+f"(d[28]), "+f"(d[29]), "+f"(d[30]), "+f"(d[31]), "+f"(d[32]), "+f"(d[33]), "+f"(d[34]), "+f"(d[35]), "+f"(d[36]), "+f"(d[37]), "+f"(d[38]), "+f"(d[39]), "+f"(d[40]), "+f"(d[41]), "+f"(d[42]), "+f"(d[43]), "+f"(d[44]), "+f"(d[45]), "+f"(d[46]), "+f"(d[47]), "+f"(d[48]), "+f"(d[49]), "+f"(d[50]), "+f"(d[51]), "+f"(d[52]), "+f"(d[53]), "+f"(d[54]), "+f"(d[55]), "+f"(d[56]), "+f"(d[57]), "+f"(d[58]), "+f"(d[59]), "+f"(d[60]), "+f"(d[61]), "+f"(d[62]), "+f"(d[63]), "+f"(d[64]), "+f"(d[65]), "+f"(d[66]), "+f"(d[67]), "+f"(d[68]), "+f"(d[69]), "+f"(d[70]), "+f"(d[71]), "+f"(d[72]), "+f"(d[73]), "+f"(d[74]), "+f"(d[75]), "+f"(d[76]), "+f"(d[77]), "+f"(d[78]), "+f"(d[79]), "+f"(d[80]), "+f"(d[81]), "+f"(d[82]), "+f"(d[83]), "+f"(d[84]), "+f"(d[85]), "+f"(d[86]), "+f"(d[87]), "+f"(d[88]), "+f"(d[89]), "+f"(d[90]), "+f"(d[91]), "+f"(d[92]), "+f"(d[93]), "+f"(d[94]), "+f"(d[95])
    : "l"(da), "l"(db), "r"(scale_d));
}

__device__ __forceinline__ void wgmma_n256(float (&d)[128], uint64_t da, uint64_t db, int scale_d) {
  asm volatile("{\n.reg .pred p;\nsetp.ne.b32 p, %130, 0;\n"
    "wgmma.mma_async.sync.aligned.m64n256k16.f32.bf16.bf16 {%0, %1, %2, %3, %4, %5, %6, %7, %8, %9, %10, %11, %12, %13, %14, %15, %16, %17, %18, %19, %20, %21, %22, %23, %24, %25, %26, %27, %28, %29, %30, %31, %32, %33, %34, %35, %36, %37, %38, %39, %40, %41, %42, %43, %44, %45, %46, %47, %48, %49, %50, %51, %52, %53, %54, %55, %56, %57, %58, %59, %60, %61, %62, %63, %64, %65, %66, %67, %68, %69, %70, %71, %72, %73, %74, %75, %76, %77, %78, %79, %80, %81, %82, %83, %84, %85, %86, %87, %88, %89, %90, %91, %92, %93, %94, %95, %96, %97, %98, %99, %100, %101, %102, %103, %104, %105, %106, %107, %108, %109, %110, %111, %112, %113, %114, %115, %116, %117, %118, %119, %120, %121, %122, %123, %124, %125, %126, %127}, %128, %129, p, 1, 1, 0, 1;\n}\n"
    : "+f"(d[0]), "+f"(d[1]), "+f"(d[2]), "+f"(d[3]), "+f"(d[4]), "+f"(d[5]), "+f"(d[6]), "+f"(d[7]), "+f"(d[8]), "+f"(d[9]), "+f"(d[10]), "+f"(d[11]), "+f"(d[12]), "+f"(d[13]), "+f"(d[14]), "+f"(d[15]), "+f"(d[16]), "+f"(d[17]), "+f"(d[18]), "+f"(d[19]), "+f"(d[20]), "+f"(d[21]), "+f"(d[22]), "+f"(d[23]), "+f"(d[24]), "+f"(d[25]), "+f"(d[26]), "+f"(d[27]), "+f"(d[28]), "+f"(d[29]), "+f"(d[30]), "+f"(d[31]), "+f"(d[32]), "+f"(d[33]), "+f"(d[34]), "+f"(d[35]), "+f"(d[36]), "+f"(d[37]), "+f"(d[38]), "+f"(d[39]), "+f"(d[40]), "+f"(d[41]), "+f"(d[42]), "+f"(d[43]), "+f"(d[44]), "+f"(d[45]), "+f"(d[46]), "+f"(d[47]), "+f"(d[48]), "+f"(d[49]), "+f"(d[50]), "+f"(d[51]), "+f"(d[52]), "+f"(d[53]), "+f"(d[54]), "+f"(d[55]), "+f"(d[56]), "+f"(d[57]), "+f"(d[58]), "+f"(d[59]), "+f"(d[60]), "+f"(d[61]), "+f"(d[62]), "+f"(d[63]), "+f"(d[64]), "+f"(d[65]), "+f"(d[66]), "+f"(d[67]), "+f"(d[68]), "+f"(d[69]), "+f"(d[70]), "+f"(d[71]), "+f"(d[72]), "+f"(d[73]), "+f"(d[74]), "+f"(d[75]), "+f"(d[76]), "+f"(d[77]), "+f"(d[78]), "+f"(d[79]), "+f"(d[80]), "+f"(d[81]), "+f"(d[82]), "+f"(d[83]), "+f"(d[84]), "+f"(d[85]), "+f"(d[86]), "+f"(d[87]), "+f"(d[88]), "+f"(d[89]), "+f"(d[90]), "+f"(d[91]), "+f"(d[92]), "+f"(d[93]), "+f"(d[94]), "+f"(d[95]), "+f"(d[96]), "+f"(d[97]), "+f"(d[98]), "+f"(d[99]), "+f"(d[100]), "+f"(d[101]), "+f"(d[102]), "+f"(d[103]), "+f"(d[104]), "+f"(d[105]), "+f"(d[106]), "+f"(d[107]), "+f"(d[108]), "+f"(d[109]), "+f"(d[110]), "+f"(d[111]), "+f"(d[112]), "+f"(d[113]), "+f"(d[114]), "+f"(d[115]), "+f"(d[116]), "+f"(d[117]), "+f"(d[118]), "+f"(d[119]), "+f"(d[120]), "+f"(d[121]), "+f"(d[122]), "+f"(d[123]), "+f"(d[124]), "+f"(d[125]), "+f"(d[126]), "+f"(d[127])
    : "l"(da), "l"(db), "r"(scale_d));
}

__device__ __forceinline__ uint32_t smem_u32(const void* p) { return (uint32_t)__cvta_generic_to_shared(p); }
__device__ __forceinline__ void mbar_init(uint32_t a, uint32_t cnt) { asm volatile("mbarrier.init.shared::cta.b64 [%0], %1;" ::"r"(a), "r"(cnt)); }
__device__ __forceinline__ void mbar_expect_tx(uint32_t a, uint32_t bytes) {
  asm volatile("mbarrier.arrive.expect_tx.shared::cta.b64 _, [%0], %1;" ::"r"(a), "r"(bytes) : "memory");
}
__device__ __forceinline__ void mbar_arrive_cluster(uint32_t a, uint32_t cta) {
  asm volatile("{\n.reg .b32 ra;\nmapa.shared::cluster.u32 ra, %0, %1;\nmbarrier.arrive.release.cluster.shared::cluster.b64 _, [ra];\n}\n" ::"r"(a), "r"(cta) : "memory");
}
__device__ __forceinline__ void mbar_wait(uint32_t a, uint32_t parity, int code) {
  uint32_t ok = 0;
#pragma unroll 1
  for (uint32_t it = 0; it < SPIN_MAX; ++it) {
    asm volatile("{\n.reg .pred p;\nmbarrier.try_wait.parity.shared::cta.b64 p, [%1], %2;\nselp.u32 %0, 1, 0, p;\n}\n" : "=r"(ok) : "r"(a), "r"(parity) : "memory");
    if (ok) return;
  }
  FAIL(code);
}
__device__ __forceinline__ void tma_load_2d(uint32_t dst, const CUtensorMap* map, int c0, int c1, uint32_t mbar) {
  asm volatile("cp.async.bulk.tensor.2d.shared::cluster.global.mbarrier::complete_tx::bytes [%0], [%1, {%3, %4}], [%2];" ::"r"(dst), "l"(map), "r"(mbar), "r"(c0), "r"(c1) : "memory");
}
__device__ __forceinline__ void tma_load_2d_mc(uint32_t dst, const CUtensorMap* map, int c0, int c1, uint32_t mbar, uint16_t mask) {
  asm volatile("cp.async.bulk.tensor.2d.shared::cluster.global.mbarrier::complete_tx::bytes.multicast::cluster [%0], [%1, {%3, %4}], [%2], %5;" ::"r"(dst), "l"(map), "r"(mbar), "r"(c0), "r"(c1), "h"(mask) : "memory");
}
__device__ __forceinline__ void wgmma_fence() { asm volatile("wgmma.fence.sync.aligned;" ::: "memory"); }
__device__ __forceinline__ void wgmma_commit() { asm volatile("wgmma.commit_group.sync.aligned;" ::: "memory"); }
template <int N> __device__ __forceinline__ void wgmma_wait() { asm volatile("wgmma.wait_group.sync.aligned %0;" ::"n"(N) : "memory"); }
__device__ __forceinline__ uint64_t make_desc(uint32_t saddr, uint32_t lbo, uint32_t sbo) {
  return (uint64_t)((saddr & 0x3FFFF) >> 4) | ((uint64_t)(lbo >> 4) << 16) | ((uint64_t)(sbo >> 4) << 32) | (1ull << 62);
}
__device__ __forceinline__ void fence_proxy_async() { asm volatile("fence.proxy.async;" ::: "memory"); }
__device__ __forceinline__ void named_bar(int id, int n) { asm volatile("bar.sync %0, %1;" ::"r"(id), "r"(n) : "memory"); }
__device__ __forceinline__ void cluster_sync() {
  asm volatile("barrier.cluster.arrive.release.aligned;\nbarrier.cluster.wait.acquire.aligned;" ::: "memory");
}
__device__ __forceinline__ unsigned ld_acquire(const unsigned* p) {
  unsigned v;
  asm volatile("ld.acquire.gpu.global.u32 %0, [%1];" : "=r"(v) : "l"(p) : "memory");
  return v;
}
__device__ __forceinline__ void flag_wait(const unsigned* p, unsigned target, int code) {
#pragma unroll 1
  for (uint32_t it = 0; it < SPIN_MAX; ++it) {
    if (ld_acquire(p) >= target) return;
    __nanosleep(32);
  }
  FAIL(code);
}
__device__ __forceinline__ void flag_add(unsigned* p) {
  asm volatile("red.release.gpu.global.add.u32 [%0], 1;" ::"l"(p) : "memory");
}
__device__ __forceinline__ void agent_exit() {
  __threadfence();
  unsigned old = atomicAdd(&g_flags[176], 1u);
  if (old == NAGENTS - 1) {
    for (int i = 0; i < 177; ++i) g_flags[i] = 0;
    __threadfence();
  }
}
__device__ __forceinline__ float bf16r(float v) { return __bfloat162float(__float2bfloat16_rn(v)); }
__device__ __forceinline__ uint32_t pack_bf16(float lo, float hi) {
  uint32_t r;
  asm("cvt.rn.bf16x2.f32 %0, %1, %2;" : "=r"(r) : "f"(hi), "f"(lo));
  return r;
}
__device__ __forceinline__ void quad_transpose(uint32_t& v0, uint32_t& v1, uint32_t& v2, uint32_t& v3, int q) {
  bool b0 = q & 1;
  uint32_t s0 = b0 ? v0 : v1, s1 = b0 ? v2 : v3;
  s0 = __shfl_xor_sync(0xffffffffu, s0, 1);
  s1 = __shfl_xor_sync(0xffffffffu, s1, 1);
  if (b0) { v0 = s0; v2 = s1; } else { v1 = s0; v3 = s1; }
  bool b1 = q & 2;
  s0 = b1 ? v0 : v2; s1 = b1 ? v1 : v3;
  s0 = __shfl_xor_sync(0xffffffffu, s0, 2);
  s1 = __shfl_xor_sync(0xffffffffu, s1, 2);
  if (b1) { v0 = s0; v1 = s1; } else { v2 = s0; v3 = s1; }
}

struct Tile { int is_h; int col; int nb; };
__device__ __forceinline__ int num_tiles(int p, int j) { return (p == 0 || j == 1) ? 6 : 5; }
__device__ __forceinline__ Tile get_tile(int p, int j, int t) {
  Tile T;
  if (p == 0) {
    if (j == 0) {
      if (t < 3) { T.is_h = 0; T.col = 256 * t; T.nb = 4; }
      else { T.is_h = 1; T.col = 128 * (t - 3); T.nb = (t == 5) ? 2 : 4; }
    } else {
      if (t < 4) { T.is_h = 0; T.col = 768 + 256 * t; T.nb = (t == 3) ? 3 : 4; }
      else { T.is_h = 1; T.col = 320 + 128 * (t - 4); T.nb = 4; }
    }
  } else {
    T.is_h = 1; T.col = 576 + (p - 1) * 1344 + (j ? 640 : 0) + 128 * t; T.nb = (j == 1 && t == 5) ? 2 : 4;
  }
  return T;
}

template <int NB> struct Acc { float a[NB * 32]; };
template <int NB> __device__ __forceinline__ void wgmma_nb(float (&d)[NB * 32], uint64_t da, uint64_t db, int sc);
template <> __device__ __forceinline__ void wgmma_nb<2>(float (&d)[64], uint64_t da, uint64_t db, int sc) { wgmma_n128(d, da, db, sc); }
template <> __device__ __forceinline__ void wgmma_nb<3>(float (&d)[96], uint64_t da, uint64_t db, int sc) { wgmma_n192(d, da, db, sc); }
template <> __device__ __forceinline__ void wgmma_nb<4>(float (&d)[128], uint64_t da, uint64_t db, int sc) { wgmma_n256(d, da, db, sc); }

struct Ctx {
  uint32_t sbase;
  uint32_t full1, empty1, full2, empty2;
  uint32_t peer;
  int wg;
  int tid;
};

template <int NB>
__device__ __forceinline__ void g1_tile(const Ctx& c, float (&acc)[NB * 32], uint32_t& it  ) {
  const uint32_t abase = c.sbase + c.wg * 8192;
  wgmma_fence();
#pragma unroll 1
  for (int kb = 0; kb < 18; ++kb) {
    uint32_t s = it % NS1, ph = (it / NS1) & 1;
    mbar_wait(c.full1 + 8 * s, ph, 0);
    uint32_t a0 = abase + (kb >> 1) * 16384 + (kb & 1) * 64;
    uint32_t b0 = c.sbase + RING1_OFF + s * ST1_BYTES;
    wgmma_nb<NB>(acc, make_desc(a0, 16, 1024), make_desc(b0, 4096, 1024), kb > 0);
    wgmma_nb<NB>(acc, make_desc(a0 + 32, 16, 1024), make_desc(b0 + 2048, 4096, 1024), 1);
    wgmma_commit();
    if (kb > 0) {
      wgmma_wait<1>();
      if (c.tid == 0) { uint32_t sp = (it - 1) % NS1; mbar_arrive_cluster(c.empty1 + 8 * sp, 0); mbar_arrive_cluster(c.empty1 + 8 * sp, 1); }
    }
    ++it;
  }
  wgmma_wait<0>();
  if (c.tid == 0) { uint32_t sp = (it - 1) % NS1; mbar_arrive_cluster(c.empty1 + 8 * sp, 0); mbar_arrive_cluster(c.empty1 + 8 * sp, 1); }
}

template <int NB>
__device__ __forceinline__ void epi_h(const Ctx& c, float (&acc)[NB * 32], int row0  , int hcol) {
  constexpr int G = NB * 4;
  const int lane = c.tid & 31, w = c.tid >> 5, q = lane & 3;
  const int r = row0 + c.wg * 64 + w * 16 + (lane >> 2);
  __nv_bfloat16* dst0 = g_act + (size_t)r * ACT_ + 576 + hcol + q * 8;
  __nv_bfloat16* dst1 = dst0 + 8 * ACT_;
  const __nv_bfloat162 zero2 = __floats2bfloat162_rn(0.f, 0.f);
#pragma unroll
  for (int a = 0; a < G / 4; ++a) {
    uint32_t v[4], u[4];
#pragma unroll
    for (int i = 0; i < 4; ++i) {
      int g = 4 * a + i;
      uint32_t g0 = pack_bf16(acc[4 * g], acc[4 * g + 1]), g1 = pack_bf16(acc[4 * g + 2], acc[4 * g + 3]);
      uint32_t u0 = pack_bf16(acc[4 * (g + G)], acc[4 * (g + G) + 1]), u1 = pack_bf16(acc[4 * (g + G) + 2], acc[4 * (g + G) + 3]);
      __nv_bfloat162 h0 = __hmul2(__hmax2(*(__nv_bfloat162*)&g0, zero2), *(__nv_bfloat162*)&u0);
      __nv_bfloat162 h1 = __hmul2(__hmax2(*(__nv_bfloat162*)&g1, zero2), *(__nv_bfloat162*)&u1);
      v[i] = *(uint32_t*)&h0; u[i] = *(uint32_t*)&h1;
    }
    quad_transpose(v[0], v[1], v[2], v[3], q);
    quad_transpose(u[0], u[1], u[2], u[3], q);
    *(uint4*)(dst0 + a * 32) = make_uint4(v[0], v[1], v[2], v[3]);
    *(uint4*)(dst1 + a * 32) = make_uint4(u[0], u[1], u[2], u[3]);
  }
}
template <int NB>
__device__ __forceinline__ void epi_qkv(const Ctx& c, float (&acc)[NB * 32], int row0, int col) {
  constexpr int G = NB * 8;
  const int lane = c.tid & 31, w = c.tid >> 5, q = lane & 3;
  const int r = row0 + c.wg * 64 + w * 16 + (lane >> 2);
  __nv_bfloat16* dst0 = g_qkv + (size_t)r * QKV_ + col + q * 8;
  __nv_bfloat16* dst1 = dst0 + 8 * QKV_;
#pragma unroll
  for (int a = 0; a < G / 4; ++a) {
    uint32_t v[4], u[4];
#pragma unroll
    for (int i = 0; i < 4; ++i) {
      int g = 4 * a + i;
      v[i] = pack_bf16(acc[4 * g], acc[4 * g + 1]); u[i] = pack_bf16(acc[4 * g + 2], acc[4 * g + 3]);
    }
    quad_transpose(v[0], v[1], v[2], v[3], q);
    quad_transpose(u[0], u[1], u[2], u[3], q);
    *(uint4*)(dst0 + a * 32) = make_uint4(v[0], v[1], v[2], v[3]);
    *(uint4*)(dst1 + a * 32) = make_uint4(u[0], u[1], u[2], u[3]);
  }
}
__device__ __forceinline__ void tile_publish(const Ctx& c, unsigned* flag) {
  fence_proxy_async();
  __threadfence();
  named_bar(1 + c.wg, 128);
  if (c.tid == 0) flag_add(flag);
}

template <int NA>
__device__ __forceinline__ void store_part(const Ctx& c, float (&acc)[NA], float* dst  ) {
#pragma unroll
  for (int g = 0; g < NA / 4; ++g) {
    *(float2*)(dst + g * 8) = make_float2(acc[4 * g], acc[4 * g + 1]);
    *(float2*)(dst + 8 * D_ + g * 8) = make_float2(acc[4 * g + 2], acc[4 * g + 3]);
  }
}

__global__ void __cluster_dims__(2, 1, 1) __launch_bounds__(384, 1)
fused_kernel(const __grid_constant__ CUtensorMap m_qkv, const __grid_constant__ CUtensorMap m_gate,
             const __grid_constant__ CUtensorMap m_up, const __grid_constant__ CUtensorMap m_wo,
             const __grid_constant__ CUtensorMap m_down, const __grid_constant__ CUtensorMap m_act,
             const __nv_bfloat16* __restrict__ x, __nv_bfloat16* __restrict__ out) {
  extern __shared__ uint8_t smem_raw[];
  const uint32_t sbase = (smem_u32(smem_raw) + 1023) & ~1023u;
  const uint32_t bars = sbase + DATA_BYTES;
  const uint32_t full1 = bars, empty1 = bars + 64, full2 = bars + 128, empty2 = bars + 192;
  const int rank = blockIdx.x & 1, cl = blockIdx.x >> 1;
  const int role = cl & 7, m = (cl >> 3) * 2 + rank, p = role >> 1, j = role & 1;
  const int row0 = m * 128;
  const int warp = __shfl_sync(0xffffffffu, (int)(threadIdx.x >> 5), 0), lane = threadIdx.x & 31;
  const int nkb2 = (p == 0) ? 18 : 21;
  const int nblk2 = j ? 4 : 5;
  const int ncol0 = j ? 320 : 0;

  if (threadIdx.x == 0) {
    for (int s = 0; s < NS1; ++s) { mbar_init(full1 + 8 * s, 1); mbar_init(empty1 + 8 * s, 4); }
    for (int s = 0; s < NS2; ++s) { mbar_init(full2 + 8 * s, 1); mbar_init(empty2 + 8 * s, 4); }
    asm volatile("fence.mbarrier_init.release.cluster;" ::: "memory");
  }
  __syncthreads();
  cluster_sync();

  if (warp < 4) {
    asm volatile("setmaxnreg.dec.sync.aligned.u32 88;");
    if (warp == 0) {
      if (lane == 0) {
        uint32_t it = 0;
        const int nt = num_tiles(p, j);
        for (int t = 0; t < nt; ++t) {
          Tile T = get_tile(p, j, t);
          for (int kb = 0; kb < 18; ++kb, ++it) {
            uint32_t s = it % NS1, ph = (it / NS1) & 1;
            mbar_wait(empty1 + 8 * s, ph ^ 1, 1);
            mbar_expect_tx(full1 + 8 * s, T.nb * 4096);
            uint32_t dst = sbase + RING1_OFF + s * ST1_BYTES;
            for (int b = rank; b < T.nb; b += 2) {
              const CUtensorMap* mp; int col;
              if (!T.is_h) { mp = &m_qkv; col = T.col + 64 * b; }
              else { int hb = T.nb >> 1; mp = (b < hb) ? &m_gate : &m_up; col = T.col + 64 * (b < hb ? b : b - hb); }
              tma_load_2d_mc(dst + b * 4096, mp, col, kb * 32, full1 + 8 * s, 3);
            }
          }
        }
        int t2 = (p == 0) ? 3 : 0, jj = 0, half = 0;
        for (int i = 0; i < nkb2; ++i) {
          uint32_t s = i % NS2, ph = (i / NS2) & 1;
          int acol; const CUtensorMap* mp; int wrow; const unsigned* fl; unsigned tgt;
          if (p == 0 && i >= 9) {
            acol = (i - 9) * 64; mp = &m_wo; wrow = acol; fl = &g_flags[128 + m]; tgt = 24;
          } else {
            int tt = (p == 0 && jj == 1) ? t2 + 1 : t2;
            Tile T = get_tile(p, jj, tt);
            int hc = T.col + 64 * half;
            acol = 576 + hc; mp = &m_down; wrow = hc; fl = &g_flags[m * 8 + 2 * p + jj]; tgt = 2 * (tt + 1);
            ++half;
            if (half == (T.nb >> 1)) {
              half = 0;
              if (jj == 0) { jj = 1; int tn = (p == 0) ? t2 + 1 : t2; if (tn >= num_tiles(p, 1)) { jj = 0; ++t2; } }
              else { jj = 0; ++t2; if (t2 >= num_tiles(p, 0)) { jj = 1; } }
            }
          }
          mbar_wait(empty2 + 8 * s, ph, 2);
          mbar_expect_tx(full2 + 8 * s, 16384 + nblk2 * 8192);
          uint32_t dst = sbase + s * ST2_BYTES;
          for (int b = 0; b < nblk2; ++b)
            tma_load_2d_mc(dst + 16384 + b * 8192 + rank * 4096, mp, ncol0 + 64 * b, wrow + 32 * rank, full2 + 8 * s, 3);
          flag_wait(fl, tgt, 4);
          fence_proxy_async();
          tma_load_2d(dst, &m_act, acol, row0, full2 + 8 * s);
        }
        agent_exit();
      }
    } else {
      const int aw = warp - 1;
      if (lane == 0) {
        flag_wait(&g_flags[m * 8 + 0], 6, 5);
        flag_wait(&g_flags[m * 8 + 1], 8, 5);
        if (role == 0 && m > 0) { flag_wait(&g_flags[(m - 1) * 8 + 0], 6, 5); flag_wait(&g_flags[(m - 1) * 8 + 1], 8, 5); }
      }
      __syncwarp();
      const float scale = 0.23570226039551584f;
      for (int rr = aw; rr < 16; rr += 3) {
        const int srow = row0 + role * 16 + rr;
        const uint32_t* qp = (const uint32_t*)(g_qkv + (size_t)srow * QKV_ + lane * 18);
        float qf[18];
#pragma unroll
        for (int d = 0; d < 9; ++d) { uint32_t v = qp[d]; qf[2 * d] = __uint_as_float(v << 16); qf[2 * d + 1] = __uint_as_float(v & 0xffff0000u); }
        float lg[8];
        float mx = -3.0e38f;
#pragma unroll
        for (int w = 0; w < 8; ++w) {
          int kr = srow - 2 * w;
          float l = -1e9f;
          if (kr >= 0) {
            const uint32_t* kp = (const uint32_t*)(g_qkv + (size_t)kr * QKV_ + 576 + lane * 18);
            float a = 0.f;
#pragma unroll
            for (int d = 0; d < 9; ++d) { uint32_t v = kp[d]; a = fmaf(qf[2 * d], __uint_as_float(v << 16), a); a = fmaf(qf[2 * d + 1], __uint_as_float(v & 0xffff0000u), a); }
            l = bf16r(bf16r(a) * scale);
          }
          lg[w] = l; mx = fmaxf(mx, l);
        }
        float sum = 0.f;
#pragma unroll
        for (int w = 0; w < 8; ++w) { lg[w] = __expf(lg[w] - mx); sum += lg[w]; }
        float inv = 1.f / sum;
        float of[18];
#pragma unroll
        for (int d = 0; d < 18; ++d) of[d] = 0.f;
#pragma unroll
        for (int w = 0; w < 8; ++w) {
          int kr = srow - 2 * w;
          if (kr >= 0) {
            float pw = bf16r(lg[w] * inv);
            const uint32_t* vp = (const uint32_t*)(g_qkv + (size_t)kr * QKV_ + 1152 + lane * 18);
#pragma unroll
            for (int d = 0; d < 9; ++d) { uint32_t v = vp[d]; of[2 * d] = fmaf(pw, __uint_as_float(v << 16), of[2 * d]); of[2 * d + 1] = fmaf(pw, __uint_as_float(v & 0xffff0000u), of[2 * d + 1]); }
          }
        }
        uint32_t* op = (uint32_t*)(g_act + (size_t)srow * ACT_ + lane * 18);
#pragma unroll
        for (int d = 0; d < 9; ++d) op[d] = pack_bf16(of[2 * d], of[2 * d + 1]);
      }
      fence_proxy_async();
      __threadfence();
      __syncwarp();
      if (lane == 0) { flag_add(&g_flags[128 + m]); agent_exit(); }
    }
  } else {
    asm volatile("setmaxnreg.inc.sync.aligned.u32 208;");
    Ctx c;
    c.sbase = sbase; c.full1 = full1; c.empty1 = empty1; c.full2 = full2; c.empty2 = empty2; c.peer = rank ^ 1;
    c.wg = (warp - 4) >> 2; c.tid = threadIdx.x - 128 - c.wg * 128;
    const int w = c.tid >> 5;
    {
      const int sub = lane >> 3, li = lane & 7;
#pragma unroll 1
      for (int half = 0; half < 2; ++half) {
      uint4 xv[2][9];
#pragma unroll
      for (int itr = 0; itr < 2; ++itr) {
        const int r = c.wg * 64 + w * 16 + half * 8 + itr * 4 + sub;
        const uint4* src = (const uint4*)(x + (size_t)(row0 + r) * D_) + li;
#pragma unroll
        for (int t = 0; t < 9; ++t) xv[itr][t] = __ldg(src + 8 * t);
      }
#pragma unroll
      for (int itr = 0; itr < 2; ++itr) {
        const int r = c.wg * 64 + w * 16 + half * 8 + itr * 4 + sub;
        float sum = 0.f;
#pragma unroll
        for (int t = 0; t < 9; ++t) {
          const uint32_t* u = (const uint32_t*)&xv[itr][t];
#pragma unroll
          for (int e = 0; e < 4; ++e) sum += __uint_as_float(u[e] << 16) + __uint_as_float(u[e] & 0xffff0000u);
        }
        sum += __shfl_xor_sync(0xffffffffu, sum, 1); sum += __shfl_xor_sync(0xffffffffu, sum, 2); sum += __shfl_xor_sync(0xffffffffu, sum, 4);
        const float mean = sum * (1.f / 576.f);
        float sq = 0.f;
#pragma unroll
        for (int t = 0; t < 9; ++t) {
          const uint32_t* u = (const uint32_t*)&xv[itr][t];
#pragma unroll
          for (int e = 0; e < 4; ++e) {
            float a = __uint_as_float(u[e] << 16) - mean, b = __uint_as_float(u[e] & 0xffff0000u) - mean;
            sq = fmaf(a, a, sq); sq = fmaf(b, b, sq);
          }
        }
        sq += __shfl_xor_sync(0xffffffffu, sq, 1); sq += __shfl_xor_sync(0xffffffffu, sq, 2); sq += __shfl_xor_sync(0xffffffffu, sq, 4);
        const float mb = bf16r(mean), vb = bf16r(sq * (1.f / 576.f));
        const float sd = bf16r(sqrtf(bf16r(vb + 1e-5f)));
        const uint32_t dsta = sbase + r * 128 + ((li ^ (r & 7)) << 4);
#pragma unroll
        for (int t = 0; t < 9; ++t) {
          const uint32_t* u = (const uint32_t*)&xv[itr][t];
          uint32_t o[4];
#pragma unroll
          for (int e = 0; e < 4; ++e) {
            float a = bf16r(__uint_as_float(u[e] << 16) - mb) / sd, b = bf16r(__uint_as_float(u[e] & 0xffff0000u) - mb) / sd;
            o[e] = pack_bf16(a, b);
          }
          asm volatile("st.shared.v4.b32 [%0], {%1, %2, %3, %4};" ::"r"(dsta + t * 16384), "r"(o[0]), "r"(o[1]), "r"(o[2]), "r"(o[3]) : "memory");
        }
      }
      }
      asm volatile("fence.proxy.async.shared::cta;" ::: "memory");
      named_bar(1 + c.wg, 128);
    }
    {
      uint32_t it = 0;
      const int nt = num_tiles(p, j);
      unsigned* myflag = &g_flags[m * 8 + role];
#pragma unroll 1
      for (int t = 0; t < nt; ++t) {
        Tile T = get_tile(p, j, t);
        if (T.nb == 4) {
          float acc[128] = {};
          g1_tile<4>(c, acc, it);
          if (T.is_h) epi_h<4>(c, acc, row0, T.col); else epi_qkv<4>(c, acc, row0, T.col);
        } else if (T.nb == 3) {
          float acc[96] = {};
          g1_tile<3>(c, acc, it);
          epi_qkv<3>(c, acc, row0, T.col);
        } else {
          float acc[64] = {};
          g1_tile<2>(c, acc, it);
          epi_h<2>(c, acc, row0, T.col);
        }
        if (t == nt - 1 && c.tid == 0) {
          for (int s = 0; s < NS2; ++s) { mbar_arrive_cluster(empty2 + 8 * s, 0); mbar_arrive_cluster(empty2 + 8 * s, 1); }
        }
        tile_publish(c, myflag);
      }
    }
    float* pdst = g_part + ((size_t)p * S_ + row0 + c.wg * 64 + w * 16 + (lane >> 2)) * D_ + ncol0 + (lane & 3) * 2;
    if (j == 0) {
      float acc1[96] = {}, acc2[64] = {};
      wgmma_fence();
#pragma unroll 1
      for (int i = 0; i < nkb2; ++i) {
        uint32_t s = i % NS2, ph = (i / NS2) & 1;
        mbar_wait(full2 + 8 * s, ph, 3);
        uint32_t a0 = sbase + s * ST2_BYTES + c.wg * 8192, b0 = sbase + s * ST2_BYTES + 16384;
#pragma unroll
        for (int k = 0; k < 4; ++k) {
          uint64_t da = make_desc(a0 + k * 32, 16, 1024);
          wgmma_n192(acc1, da, make_desc(b0 + k * 2048, 8192, 1024), (i | k) != 0);
          wgmma_n128(acc2, da, make_desc(b0 + 3 * 8192 + k * 2048, 8192, 1024), (i | k) != 0);
        }
        wgmma_commit();
        if (i > 0) {
          wgmma_wait<1>();
          if (c.tid == 0 && i - 1 + NS2 < nkb2) { uint32_t sp = (i - 1) % NS2; mbar_arrive_cluster(empty2 + 8 * sp, 0); mbar_arrive_cluster(empty2 + 8 * sp, 1); }
        }
      }
      wgmma_wait<0>();
      store_part<96>(c, acc1, pdst);
      store_part<64>(c, acc2, pdst + 192);
    } else {
      float acc[128] = {};
      wgmma_fence();
#pragma unroll 1
      for (int i = 0; i < nkb2; ++i) {
        uint32_t s = i % NS2, ph = (i / NS2) & 1;
        mbar_wait(full2 + 8 * s, ph, 3);
        uint32_t a0 = sbase + s * ST2_BYTES + c.wg * 8192, b0 = sbase + s * ST2_BYTES + 16384;
#pragma unroll
        for (int k = 0; k < 4; ++k)
          wgmma_n256(acc, make_desc(a0 + k * 32, 16, 1024), make_desc(b0 + k * 2048, 8192, 1024), (i | k) != 0);
        wgmma_commit();
        if (i > 0) {
          wgmma_wait<1>();
          if (c.tid == 0 && i - 1 + NS2 < nkb2) { uint32_t sp = (i - 1) % NS2; mbar_arrive_cluster(empty2 + 8 * sp, 0); mbar_arrive_cluster(empty2 + 8 * sp, 1); }
        }
      }
      wgmma_wait<0>();
      store_part<128>(c, acc, pdst);
    }
    __threadfence();
    named_bar(1 + c.wg, 128);
    unsigned* pf = &g_flags[144 + m * 2 + j];
    if (c.tid == 0) flag_add(pf);
    if (lane == 0) flag_wait(pf, 8, 6);
    __syncwarp();
    {
      const int ncq = (j ? 256 : 320) / 4;
      const int tot = 32 * ncq;
      const int t256 = c.wg * 128 + c.tid;
      for (int e = t256; e < tot; e += 256) {
        int r = e / ncq, cq = e - r * ncq;
        size_t off = (size_t)(row0 + 32 * p + r) * D_ + ncol0 + cq * 4;
        float4 a = __ldcg((const float4*)(g_part + off));
        float4 b = __ldcg((const float4*)(g_part + (size_t)S_ * D_ + off));
        float4 cc = __ldcg((const float4*)(g_part + (size_t)2 * S_ * D_ + off));
        float4 d = __ldcg((const float4*)(g_part + (size_t)3 * S_ * D_ + off));
        uint2 xv = __ldg((const uint2*)(x + off));
        float o0 = (a.x + b.x) + (cc.x + d.x) + __uint_as_float(xv.x << 16);
        float o1 = (a.y + b.y) + (cc.y + d.y) + __uint_as_float(xv.x & 0xffff0000u);
        float o2 = (a.z + b.z) + (cc.z + d.z) + __uint_as_float(xv.y << 16);
        float o3 = (a.w + b.w) + (cc.w + d.w) + __uint_as_float(xv.y & 0xffff0000u);
        *(uint2*)(out + off) = make_uint2(pack_bf16(o0, o1), pack_bf16(o2, o3));
      }
    }
    named_bar(1 + c.wg, 128);
    if (c.tid == 0) agent_exit();
  }
}

typedef CUresult (*EncodeFn)(CUtensorMap*, CUtensorMapDataType, cuuint32_t, void*, const cuuint64_t*, const cuuint64_t*,
                             const cuuint32_t*, const cuuint32_t*, CUtensorMapInterleave, CUtensorMapSwizzle,
                             CUtensorMapL2promotion, CUtensorMapFloatOOBfill);

static void make_map(EncodeFn enc, CUtensorMap* mp, const void* ptr, int rows, int cols, int box_rows) {
  cuuint64_t dims[2] = {(cuuint64_t)cols, (cuuint64_t)rows};
  cuuint64_t strides[1] = {(cuuint64_t)cols * 2};
  cuuint32_t box[2] = {64, (cuuint32_t)box_rows};
  cuuint32_t es[2] = {1, 1};
  enc(mp, CU_TENSOR_MAP_DATA_TYPE_BFLOAT16, 2, (void*)ptr, dims, strides, box, es, CU_TENSOR_MAP_INTERLEAVE_NONE,
      CU_TENSOR_MAP_SWIZZLE_128B, CU_TENSOR_MAP_L2_PROMOTION_L2_256B, CU_TENSOR_MAP_FLOAT_OOB_FILL_NONE);
}

extern "C" void kernel_launch(void* const* d_in, const int* in_sizes, int n_in, void* d_out, int out_size) {
  static EncodeFn enc = nullptr;
  static void* act_ptr = nullptr;
  if (!enc) {
    void* fn = nullptr;
    cudaDriverEntryPointQueryResult qr;
    cudaGetDriverEntryPoint("cuTensorMapEncodeTiled", &fn, cudaEnableDefault, &qr);
    enc = (EncodeFn)fn;
    cudaGetSymbolAddress(&act_ptr, g_act);
    cudaFuncSetAttribute(fused_kernel, cudaFuncAttributeMaxDynamicSharedMemorySize, SMEM_BYTES);
  }
  const __nv_bfloat16* x = (const __nv_bfloat16*)d_in[0];
  CUtensorMap m_qkv, m_gate, m_up, m_wo, m_down, m_act;
  make_map(enc, &m_qkv, d_in[1], D_, QKV_, 32);
  make_map(enc, &m_wo, d_in[2], D_, D_, 32);
  make_map(enc, &m_gate, d_in[4], D_, F_, 32);
  make_map(enc, &m_up, d_in[5], D_, F_, 32);
  make_map(enc, &m_down, d_in[6], F_, D_, 32);
  make_map(enc, &m_act, act_ptr, S_, ACT_, 128);
  fused_kernel<<<128, 384, SMEM_BYTES>>>(m_qkv, m_gate, m_up, m_wo, m_down, m_act, x, (__nv_bfloat16*)d_out);
}
```

```cpp
#include <cuda_runtime.h>
#include <cuda_bf16.h>
#include <cuda.h>
#include <stdint.h>

constexpr int S_ = 2048, D_ = 576, F_ = 4608, QKV_ = 1728, ACT_ = 5184;
constexpr int NS1 = 5;
constexpr int NS2 = 4;
constexpr int XN_BYTES = 9 * 16384;
constexpr int RING1_OFF = XN_BYTES;
constexpr int ST1_BYTES = 16384;
constexpr int ST2_BYTES = 57344;
constexpr int DATA_BYTES = 229376;
constexpr int SMEM_BYTES = DATA_BYTES + 1024 + 512;
constexpr int NAGENTS = 128 * 4;
#define MC 1

__device__ __align__(1024) __nv_bfloat16 g_qkv[S_ * QKV_];
__device__ __align__(1024) __nv_bfloat16 g_act[S_ * ACT_];
__device__ __align__(1024) uint4 g_xch[16 * 2 * 4 * 128 * 40];
__device__ unsigned int g_flags[288];
#define TS(i)
#define TS2(i)
#define FAIL(code) __trap()
#define SPIN_MAX (1u << 24)

__device__ __forceinline__ void wgmma_n64(float (&d)[32], uint64_t da, uint64_t db, int scale_d) {
  asm volatile("{\n.reg .pred p;\nsetp.ne.b32 p, %34, 0;\n"
    "wgmma.mma_async.sync.aligned.m64n64k16.f32.bf16.bf16 {%0, %1, %2, %3, %4, %5, %6, %7, %8, %9, %10, %11, %12, %13, %14, %15, %16, %17, %18, %19, %20, %21, %22, %23, %24, %25, %26, %27, %28, %29, %30, %31}, %32, %33, p, 1, 1, 0, 1;\n}\n"
    : "+f"(d[0]), "+f"(d[1]), "+f"(d[2]), "+f"(d[3]), "+f"(d[4]), "+f"(d[5]), "+f"(d[6]), "+f"(d[7]), "+f"(d[8]), "+f"(d[9]), "+f"(d[10]), "+f"(d[11]), "+f"(d[12]), "+f"(d[13]), "+f"(d[14]), "+f"(d[15]), "+f"(d[16]), "+f"(d[17]), "+f"(d[18]), "+f"(d[19]), "+f"(d[20]), "+f"(d[21]), "+f"(d[22]), "+f"(d[23]), "+f"(d[24]), "+f"(d[25]), "+f"(d[26]), "+f"(d[27]), "+f"(d[28]), "+f"(d[29]), "+f"(d[30]), "+f"(d[31])
    : "l"(da), "l"(db), "r"(scale_d));
}

__device__ __forceinline__ void wgmma_n128(float (&d)[64], uint64_t da, uint64_t db, int scale_d) {
  asm volatile("{\n.reg .pred p;\nsetp.ne.b32 p, %66, 0;\n"
    "wgmma.mma_async.sync.aligned.m64n128k16.f32.bf16.bf16 {%0, %1, %2, %3, %4, %5, %6, %7, %8, %9, %10, %11, %12, %13, %14, %15, %16, %17, %18, %19, %20, %21, %22, %23, %24, %25, %26, %27, %28, %29, %30, %31, %32, %33, %34, %35, %36, %37, %38, %39, %40, %41, %42, %43, %44, %45, %46, %47, %48, %49, %50, %51, %52, %53, %54, %55, %56, %57, %58, %59, %60, %61, %62, %63}, %64, %65, p, 1, 1, 0, 1;\n}\n"
    : "+f"(d[0]), "+f"(d[1]), "+f"(d[2]), "+f"(d[3]), "+f"(d[4]), "+f"(d[5]), "+f"(d[6]), "+f"(d[7]), "+f"(d[8]), "+f"(d[9]), "+f"(d[10]), "+f"(d[11]), "+f"(d[12]), "+f"(d[13]), "+f"(d[14]), "+f"(d[15]), "+f"(d[16]), "+f"(d[17]), "+f"(d[18]), "+f"(d[19]), "+f"(d[20]), "+f"(d[21]), "+f"(d[22]), "+f"(d[23]), "+f"(d[24]), "+f"(d[25]), "+f"(d[26]), "+f"(d[27]), "+f"(d[28]), "+f"(d[29]), "+f"(d[30]), "+f"(d[31]), "+f"(d[32]), "+f"(d[33]), "+f"(d[34]), "+f"(d[35]), "+f"(d[36]), "+f"(d[37]), "+f"(d[38]), "+f"(d[39]), "+f"(d[40]), "+f"(d[41]), "+f"(d[42]), "+f"(d[43]), "+f"(d[44]), "+f"(d[45]), "+f"(d[46]), "+f"(d[47]), "+f"(d[48]), "+f"(d[49]), "+f"(d[50]), "+f"(d[51]), "+f"(d[52]), "+f"(d[53]), "+f"(d[54]), "+f"(d[55]), "+f"(d[56]), "+f"(d[57]), "+f"(d[58]), "+f"(d[59]), "+f"(d[60]), "+f"(d[61]), "+f"(d[62]), "+f"(d[63])
    : "l"(da), "l"(db), "r"(scale_d));
}

__device__ __forceinline__ void wgmma_n192(float (&d)[96], uint64_t da, uint64_t db, int scale_d) {
  asm volatile("{\n.reg .pred p;\nsetp.ne.b32 p, %98, 0;\n"
    "wgmma.mma_async.sync.aligned.m64n192k16.f32.bf16.bf16 {%0, %1, %2, %3, %4, %5, %6, %7, %8, %9, %10, %11, %12, %13, %14, %15, %16, %17, %18, %19, %20, %21, %22, %23, %24, %25, %26, %27, %28, %29, %30, %31, %32, %33, %34, %35, %36, %37, %38, %39, %40, %41, %42, %43, %44, %45, %46, %47, %48, %49, %50, %51, %52, %53, %54, %55, %56, %57, %58, %59, %60, %61, %62, %63, %64, %65, %66, %67, %68, %69, %70, %71, %72, %73, %74, %75, %76, %77, %78, %79, %80, %81, %82, %83, %84, %85, %86, %87, %88, %89, %90, %91, %92, %93, %94, %95}, %96, %97, p, 1, 1, 0, 1;\n}\n"
    : "+f"(d[0]), "+f"(d[1]), "+f"(d[2]), "+f"(d[3]), "+f"(d[4]), "+f"(d[5]), "+f"(d[6]), "+f"(d[7]), "+f"(d[8]), "+f"(d[9]), "+f"(d[10]), "+f"(d[11]), "+f"(d[12]), "+f"(d[13]), "+f"(d[14]), "+f"(d[15]), "+f"(d[16]), "+f"(d[17]), "+f"(d[18]), "+f"(d[19]), "+f"(d[20]), "+f"(d[21]), "+f"(d[22]), "+f"(d[23]), "+f"(d[24]), "+f"(d[25]), "+f"(d[26]), "+f"(d[27]), "+f"(d[28]), "+f"(d[29]), "+f"(d[30]), "+f"(d[31]), "+f"(d[32]), "+f"(d[33]), "+f"(d[34]), "+f"(d[35]), "+f"(d[36]), "+f"(d[37]), "+f"(d[38]), "+f"(d[39]), "+f"(d[40]), "+f"(d[41]), "+f"(d[42]), "+f"(d[43]), "+f"(d[44]), "+f"(d[45]), "+f"(d[46]), "+f"(d[47]), "+f"(d[48]), "+f"(d[49]), "+f"(d[50]), "+f"(d[51]), "+f"(d[52]), "+f"(d[53]), "+f"(d[54]), "+f"(d[55]), "+f"(d[56]), "+f"(d[57]), "+f"(d[58]), "+f"(d[59]), "+f"(d[60]), "+f"(d[61]), "+f"(d[62]), "+f"(d[63]), "+f"(d[64]), "+f"(d[65]), "+f"(d[66]), "+f"(d[67]), "+f"(d[68]), "+f"(d[69]), "+f"(d[70]), "+f"(d[71]), "+f"(d[72]), "+f"(d[73]), "+f"(d[74]), "+f"(d[75]), "+f"(d[76]), "+f"(d[77]), "+f"(d[78]), "+f"(d[79]), "+f"(d[80]), "+f"(d[81]), "+f"(d[82]), "+f"(d[83]), "+f"(d[84]), "+f"(d[85]), "+f"(d[86]), "+f"(d[87]), "+f"(d[88]), "+f"(d[89]), "+f"(d[90]), "+f"(d[91]), "+f"(d[92]), "+f"(d[93]), "+f"(d[94]), "+f"(d[95])
    : "l"(da), "l"(db), "r"(scale_d));
}

__device__ __forceinline__ void wgmma_n256(float (&d)[128], uint64_t da, uint64_t db, int scale_d) {
  asm volatile("{\n.reg .pred p;\nsetp.ne.b32 p, %130, 0;\n"
    "wgmma.mma_async.sync.aligned.m64n256k16.f32.bf16.bf16 {%0, %1, %2, %3, %4, %5, %6, %7, %8, %9, %10, %11, %12, %13, %14, %15, %16, %17, %18, %19, %20, %21, %22, %23, %24, %25, %26, %27, %28, %29, %30, %31, %32, %33, %34, %35, %36, %37, %38, %39, %40, %41, %42, %43, %44, %45, %46, %47, %48, %49, %50, %51, %52, %53, %54, %55, %56, %57, %58, %59, %60, %61, %62, %63, %64, %65, %66, %67, %68, %69, %70, %71, %72, %73, %74, %75, %76, %77, %78, %79, %80, %81, %82, %83, %84, %85, %86, %87, %88, %89, %90, %91, %92, %93, %94, %95, %96, %97, %98, %99, %100, %101, %102, %103, %104, %105, %106, %107, %108, %109, %110, %111, %112, %113, %114, %115, %116, %117, %118, %119, %120, %121, %122, %123, %124, %125, %126, %127}, %128, %129, p, 1, 1, 0, 1;\n}\n"
    : "+f"(d[0]), "+f"(d[1]), "+f"(d[2]), "+f"(d[3]), "+f"(d[4]), "+f"(d[5]), "+f"(d[6]), "+f"(d[7]), "+f"(d[8]), "+f"(d[9]), "+f"(d[10]), "+f"(d[11]), "+f"(d[12]), "+f"(d[13]), "+f"(d[14]), "+f"(d[15]), "+f"(d[16]), "+f"(d[17]), "+f"(d[18]), "+f"(d[19]), "+f"(d[20]), "+f"(d[21]), "+f"(d[22]), "+f"(d[23]), "+f"(d[24]), "+f"(d[25]), "+f"(d[26]), "+f"(d[27]), "+f"(d[28]), "+f"(d[29]), "+f"(d[30]), "+f"(d[31]), "+f"(d[32]), "+f"(d[33]), "+f"(d[34]), "+f"(d[35]), "+f"(d[36]), "+f"(d[37]), "+f"(d[38]), "+f"(d[39]), "+f"(d[40]), "+f"(d[41]), "+f"(d[42]), "+f"(d[43]), "+f"(d[44]), "+f"(d[45]), "+f"(d[46]), "+f"(d[47]), "+f"(d[48]), "+f"(d[49]), "+f"(d[50]), "+f"(d[51]), "+f"(d[52]), "+f"(d[53]), "+f"(d[54]), "+f"(d[55]), "+f"(d[56]), "+f"(d[57]), "+f"(d[58]), "+f"(d[59]), "+f"(d[60]), "+f"(d[61]), "+f"(d[62]), "+f"(d[63]), "+f"(d[64]), "+f"(d[65]), "+f"(d[66]), "+f"(d[67]), "+f"(d[68]), "+f"(d[69]), "+f"(d[70]), "+f"(d[71]), "+f"(d[72]), "+f"(d[73]), "+f"(d[74]), "+f"(d[75]), "+f"(d[76]), "+f"(d[77]), "+f"(d[78]), "+f"(d[79]), "+f"(d[80]), "+f"(d[81]), "+f"(d[82]), "+f"(d[83]), "+f"(d[84]), "+f"(d[85]), "+f"(d[86]), "+f"(d[87]), "+f"(d[88]), "+f"(d[89]), "+f"(d[90]), "+f"(d[91]), "+f"(d[92]), "+f"(d[93]), "+f"(d[94]), "+f"(d[95]), "+f"(d[96]), "+f"(d[97]), "+f"(d[98]), "+f"(d[99]), "+f"(d[100]), "+f"(d[101]), "+f"(d[102]), "+f"(d[103]), "+f"(d[104]), "+f"(d[105]), "+f"(d[106]), "+f"(d[107]), "+f"(d[108]), "+f"(d[109]), "+f"(d[110]), "+f"(d[111]), "+f"(d[112]), "+f"(d[113]), "+f"(d[114]), "+f"(d[115]), "+f"(d[116]), "+f"(d[117]), "+f"(d[118]), "+f"(d[119]), "+f"(d[120]), "+f"(d[121]), "+f"(d[122]), "+f"(d[123]), "+f"(d[124]), "+f"(d[125]), "+f"(d[126]), "+f"(d[127])
    : "l"(da), "l"(db), "r"(scale_d));
}

__device__ __forceinline__ uint32_t smem_u32(const void* p) { return (uint32_t)__cvta_generic_to_shared(p); }
__device__ __forceinline__ void mbar_init(uint32_t a, uint32_t cnt) { asm volatile("mbarrier.init.shared::cta.b64 [%0], %1;" ::"r"(a), "r"(cnt)); }
__device__ __forceinline__ void mbar_expect_tx(uint32_t a, uint32_t bytes) {
  asm volatile("mbarrier.arrive.expect_tx.shared::cta.b64 _, [%0], %1;" ::"r"(a), "r"(bytes) : "memory");
}
__device__ __forceinline__ void mbar_arrive_cluster(uint32_t a, uint32_t cta) {
  asm volatile("{\n.reg .b32 ra;\nmapa.shared::cluster.u32 ra, %0, %1;\nmbarrier.arrive.shared::cluster.b64 _, [ra];\n}\n" ::"r"(a), "r"(cta) : "memory");
}
__device__ __forceinline__ void mbar_arrive_both(uint32_t a) {
  mbar_arrive_cluster(a, 0); mbar_arrive_cluster(a, 1);
}
__device__ __forceinline__ void mbar_wait(uint32_t a, uint32_t parity, int code) {
  uint32_t ok = 0;
#pragma unroll 1
  for (uint32_t it = 0; it < SPIN_MAX; ++it) {
    asm volatile("{\n.reg .pred p;\nmbarrier.try_wait.parity.shared::cta.b64 p, [%1], %2;\nselp.u32 %0, 1, 0, p;\n}\n" : "=r"(ok) : "r"(a), "r"(parity) : "memory");
    if (ok) return;
  }
  FAIL(code);
}
__device__ __forceinline__ bool mbar_test(uint32_t a, uint32_t parity) {
  uint32_t ok;
  asm volatile("{\n.reg .pred p;\nmbarrier.test_wait.parity.shared::cta.b64 p, [%1], %2;\nselp.u32 %0, 1, 0, p;\n}\n" : "=r"(ok) : "r"(a), "r"(parity) : "memory");
  return __all_sync(0xffffffffu, ok != 0);
}
__device__ __forceinline__ void tma_load_2d(uint32_t dst, const CUtensorMap* map, int c0, int c1, uint32_t mbar) {
  asm volatile("cp.async.bulk.tensor.2d.shared::cluster.global.mbarrier::complete_tx::bytes [%0], [%1, {%3, %4}], [%2];" ::"r"(dst), "l"(map), "r"(mbar), "r"(c0), "r"(c1) : "memory");
}
__device__ __forceinline__ void tma_load_2d_mc(uint32_t dst, const CUtensorMap* map, int c0, int c1, uint32_t mbar, uint16_t mask) {
  asm volatile("cp.async.bulk.tensor.2d.shared::cluster.global.mbarrier::complete_tx::bytes.multicast::cluster [%0], [%1, {%3, %4}], [%2], %5;" ::"r"(dst), "l"(map), "r"(mbar), "r"(c0), "r"(c1), "h"(mask) : "memory");
}
__device__ __forceinline__ void tma_load_3d_mc(uint32_t dst, const CUtensorMap* map, int c0, int c1, int c2, uint32_t mbar, uint16_t mask) {
  asm volatile("cp.async.bulk.tensor.3d.shared::cluster.global.mbarrier::complete_tx::bytes.multicast::cluster [%0], [%1, {%3, %4, %5}], [%2], %6;" ::"r"(dst), "l"(map), "r"(mbar), "r"(c0), "r"(c1), "r"(c2), "h"(mask) : "memory");
}
__device__ __forceinline__ void wgmma_fence() { asm volatile("wgmma.fence.sync.aligned;" ::: "memory"); }
__device__ __forceinline__ void wgmma_commit() { asm volatile("wgmma.commit_group.sync.aligned;" ::: "memory"); }
template <int N> __device__ __forceinline__ void wgmma_wait() { asm volatile("wgmma.wait_group.sync.aligned %0;" ::"n"(N) : "memory"); }
__device__ __forceinline__ uint64_t make_desc(uint32_t saddr, uint32_t lbo, uint32_t sbo) {
  return (uint64_t)((saddr & 0x3FFFF) >> 4) | ((uint64_t)(lbo >> 4) << 16) | ((uint64_t)(sbo >> 4) << 32) | (1ull << 62);
}
__device__ __forceinline__ void fence_proxy_async() { asm volatile("fence.proxy.async.global;" ::: "memory"); }
__device__ __forceinline__ void named_bar(int id, int n) { asm volatile("bar.sync %0, %1;" ::"r"(id), "r"(n) : "memory"); }
__device__ __forceinline__ void cluster_sync() {
  asm volatile("barrier.cluster.arrive.release.aligned;\nbarrier.cluster.wait.acquire.aligned;" ::: "memory");
}
__device__ __forceinline__ unsigned ld_acquire(const unsigned* p) {
  unsigned v;
  asm volatile("ld.acquire.gpu.global.u32 %0, [%1];" : "=r"(v) : "l"(p) : "memory");
  return v;
}
__device__ __forceinline__ unsigned flag_wait(const unsigned* p, unsigned target, int code) {
#pragma unroll 1
  for (uint32_t it = 0; it < SPIN_MAX; ++it) {
    unsigned v = ld_acquire(p);
    if (v >= target) return v;
    __nanosleep(64);
  }
  FAIL(code);
  return 0;
}
__device__ __forceinline__ void flag_add(unsigned* p) {
  asm volatile("red.release.gpu.global.add.u32 [%0], 1;" ::"l"(p) : "memory");
}
__device__ __forceinline__ void agent_exit() {
  __threadfence();
  unsigned old = atomicAdd(&g_flags[272], 1u);
  if (old == NAGENTS - 1) {
    for (int i = 0; i < 273; ++i) g_flags[i] = 0;
    __threadfence();
  }
}
__device__ __forceinline__ float bf16r(float v) { return __bfloat162float(__float2bfloat16_rn(v)); }
__device__ __forceinline__ uint32_t pack_bf16(float lo, float hi) {
  uint32_t r;
  asm("cvt.rn.bf16x2.f32 %0, %1, %2;" : "=r"(r) : "f"(hi), "f"(lo));
  return r;
}
__device__ __forceinline__ void quad_transpose(uint32_t& v0, uint32_t& v1, uint32_t& v2, uint32_t& v3, int q) {
  bool b0 = q & 1;
  uint32_t s0 = b0 ? v0 : v1, s1 = b0 ? v2 : v3;
  s0 = __shfl_xor_sync(0xffffffffu, s0, 1);
  s1 = __shfl_xor_sync(0xffffffffu, s1, 1);
  if (b0) { v0 = s0; v2 = s1; } else { v1 = s0; v3 = s1; }
  bool b1 = q & 2;
  s0 = b1 ? v0 : v2; s1 = b1 ? v1 : v3;
  s0 = __shfl_xor_sync(0xffffffffu, s0, 2);
  s1 = __shfl_xor_sync(0xffffffffu, s1, 2);
  if (b1) { v0 = s0; v1 = s1; } else { v2 = s0; v3 = s1; }
}

struct Tile { int is_h; int col; int nb; };
__device__ __forceinline__ int num_tiles(int j) { return j ? 6 : 5; }
__device__ __forceinline__ Tile get_tile(int p, int j, int t) {
  Tile T;
  if (t == 0) {
    T.is_h = 0;
    if (j == 0) { T.col = 256 * p; T.nb = 4; }
    else { T.col = 1024 + 192 * p; T.nb = (p == 3) ? 2 : 3; }
  } else {
    T.is_h = 1; T.col = 128 * (9 * p + (j ? 4 : 0) + (t - 1)); T.nb = 4;
  }
  return T;
}

template <int NB> struct Acc { float a[NB * 32]; };
template <int NB> __device__ __forceinline__ void wgmma_nb(float (&d)[NB * 32], uint64_t da, uint64_t db, int sc);
template <> __device__ __forceinline__ void wgmma_nb<2>(float (&d)[64], uint64_t da, uint64_t db, int sc) { wgmma_n128(d, da, db, sc); }
template <> __device__ __forceinline__ void wgmma_nb<3>(float (&d)[96], uint64_t da, uint64_t db, int sc) { wgmma_n192(d, da, db, sc); }
template <> __device__ __forceinline__ void wgmma_nb<4>(float (&d)[128], uint64_t da, uint64_t db, int sc) { wgmma_n256(d, da, db, sc); }

struct Ctx {
  uint32_t sbase;
  uint32_t full1, empty1, full2, empty2;
  uint32_t peer;
  int wg;
  int tid;
};

__device__ __forceinline__ void publish(unsigned* flag) {
  __threadfence();
  __syncwarp();
  if ((threadIdx.x & 31) == 0) flag_add(flag);
}
template <int NB>
__device__ __forceinline__ void g1_tile(const Ctx& c, float (&acc)[NB * 32], uint32_t& it  , unsigned* pend) {
  const uint32_t abase = c.sbase + c.wg * 8192;
  wgmma_fence();
#pragma unroll 1
  for (int kb = 0; kb < 18; ++kb) {
    uint32_t s = it % NS1, ph = (it / NS1) & 1;
    bool rel = false;
    if (kb > 0 && !mbar_test(c.full1 + 8 * s, ph)) {
      wgmma_wait<0>();
      if (c.tid == 0) { uint32_t sp = (it - 1) % NS1; mbar_arrive_both(c.empty1 + 8 * sp); }
      rel = true;
    }
    mbar_wait(c.full1 + 8 * s, ph, 0);
    uint32_t a0 = abase + (kb >> 1) * 16384 + (kb & 1) * 64;
    uint32_t b0 = c.sbase + RING1_OFF + s * ST1_BYTES;
    wgmma_nb<NB>(acc, make_desc(a0, 16, 1024), make_desc(b0, 4096, 1024), kb > 0);
    wgmma_nb<NB>(acc, make_desc(a0 + 32, 16, 1024), make_desc(b0 + 2048, 4096, 1024), 1);
    wgmma_commit();
    if (kb > 0 && !rel) {
      wgmma_wait<1>();
      if (c.tid == 0) { uint32_t sp = (it - 1) % NS1; mbar_arrive_both(c.empty1 + 8 * sp); }
    }
    ++it;
  }
  wgmma_wait<0>();
  if (c.tid == 0) { uint32_t sp = (it - 1) % NS1; mbar_arrive_both(c.empty1 + 8 * sp); }
}

template <int NB>
__device__ __forceinline__ void epi_h(const Ctx& c, float (&acc)[NB * 32], int row0  , int hcol) {
  constexpr int G = NB * 4;
  const int lane = c.tid & 31, w = c.tid >> 5, q = lane & 3;
  const int r = row0 + c.wg * 64 + w * 16 + (lane >> 2);
  __nv_bfloat16* dst0 = g_act + (size_t)r * ACT_ + 576 + hcol + q * 8;
  __nv_bfloat16* dst1 = dst0 + 8 * ACT_;
  const __nv_bfloat162 zero2 = __floats2bfloat162_rn(0.f, 0.f);
#pragma unroll
  for (int a = 0; a < G / 4; ++a) {
    uint32_t v[4], u[4];
#pragma unroll
    for (int i = 0; i < 4; ++i) {
      int g = 4 * a + i;
      uint32_t g0 = pack_bf16(acc[4 * g], acc[4 * g + 1]), g1 = pack_bf16(acc[4 * g + 2], acc[4 * g + 3]);
      uint32_t u0 = pack_bf16(acc[4 * (g + G)], acc[4 * (g + G) + 1]), u1 = pack_bf16(acc[4 * (g + G) + 2], acc[4 * (g + G) + 3]);
      __nv_bfloat162 h0 = __hmul2(__hmax2(*(__nv_bfloat162*)&g0, zero2), *(__nv_bfloat162*)&u0);
      __nv_bfloat162 h1 = __hmul2(__hmax2(*(__nv_bfloat162*)&g1, zero2), *(__nv_bfloat162*)&u1);
      v[i] = *(uint32_t*)&h0; u[i] = *(uint32_t*)&h1;
    }
    quad_transpose(v[0], v[1], v[2], v[3], q);
    quad_transpose(u[0], u[1], u[2], u[3], q);
    *(uint4*)(dst0 + a * 32) = make_uint4(v[0], v[1], v[2], v[3]);
    *(uint4*)(dst1 + a * 32) = make_uint4(u[0], u[1], u[2], u[3]);
  }
}
template <int NB>
__device__ __forceinline__ void epi_qkv(const Ctx& c, float (&acc)[NB * 32], int row0, int col) {
  constexpr int G = NB * 8;
  const int lane = c.tid & 31, w = c.tid >> 5, q = lane & 3;
  const int r = row0 + c.wg * 64 + w * 16 + (lane >> 2);
  __nv_bfloat16* dst0 = g_qkv + (size_t)r * QKV_ + col + q * 8;
  __nv_bfloat16* dst1 = dst0 + 8 * QKV_;
#pragma unroll
  for (int a = 0; a < G / 4; ++a) {
    uint32_t v[4], u[4];
#pragma unroll
    for (int i = 0; i < 4; ++i) {
      int g = 4 * a + i;
      v[i] = pack_bf16(acc[4 * g], acc[4 * g + 1]); u[i] = pack_bf16(acc[4 * g + 2], acc[4 * g + 3]);
    }
    quad_transpose(v[0], v[1], v[2], v[3], q);
    quad_transpose(u[0], u[1], u[2], u[3], q);
    *(uint4*)(dst0 + a * 32) = make_uint4(v[0], v[1], v[2], v[3]);
    *(uint4*)(dst1 + a * 32) = make_uint4(u[0], u[1], u[2], u[3]);
  }
}
__device__ __forceinline__ void mbar_arrive_local(uint32_t a) { asm volatile("mbarrier.arrive.shared::cta.b64 _, [%0];" ::"r"(a) : "memory"); }

template <int NA>
__device__ __forceinline__ void acc_to_smem(float (&acc)[NA], uint32_t a0  , uint32_t pitch) {
#pragma unroll
  for (int g = 0; g < NA / 4; ++g) {
    asm volatile("st.shared.v2.f32 [%0], {%1, %2};" ::"r"(a0 + g * 32), "f"(acc[4 * g]), "f"(acc[4 * g + 1]) : "memory");
    asm volatile("st.shared.v2.f32 [%0], {%1, %2};" ::"r"(a0 + 8 * pitch + g * 32), "f"(acc[4 * g + 2]), "f"(acc[4 * g + 3]) : "memory");
  }
}
__device__ __forceinline__ float4 lds128(uint32_t a) {
  float4 v;
  asm volatile("ld.shared.v4.f32 {%0, %1, %2, %3}, [%4];" : "=f"(v.x), "=f"(v.y), "=f"(v.z), "=f"(v.w) : "r"(a) : "memory");
  return v;
}

__device__ __forceinline__ void mma16816(float (&c)[4], uint32_t a0, uint32_t a1, uint32_t a2, uint32_t a3, uint32_t b0, uint32_t b1) {
  asm volatile("mma.sync.aligned.m16n8k16.row.col.f32.bf16.bf16.f32 {%0,%1,%2,%3}, {%4,%5,%6,%7}, {%8,%9}, {%0,%1,%2,%3};"
               : "+f"(c[0]), "+f"(c[1]), "+f"(c[2]), "+f"(c[3]) : "r"(a0), "r"(a1), "r"(a2), "r"(a3), "r"(b0), "r"(b1));
}
__device__ __forceinline__ uint32_t movm(uint32_t a) {
  uint32_t d;
  asm volatile("movmatrix.sync.aligned.m8n8.trans.b16 %0, %1;" : "=r"(d) : "r"(a));
  return d;
}
struct HeadRegs { uint32_t q[2][3], k[4][3], v[4][3]; };
__device__ __forceinline__ void load_head(HeadRegs& R, int h, int qrow, int g, int t) {
  const int o = h & 1;
  const int wp = 9 * h + o + 2 * t, wt = 9 * h + (o ? 0 : 8);
#pragma unroll
  for (int r = 0; r < 2; ++r) {
    const uint32_t* p = (const uint32_t*)(g_qkv + (size_t)(qrow + g + 8 * r) * QKV_);
    uint2 a = *(const uint2*)(p + wp);
    R.q[r][0] = a.x; R.q[r][1] = a.y; R.q[r][2] = t == 0 ? p[wt] : 0u;
  }
#pragma unroll
  for (int nt = 0; nt < 4; ++nt) {
    const int jj = 8 * nt + g, kr = qrow - 14 + jj;
    const bool ok = (kr >= 0) && (jj < 30);
    const uint32_t* p = (const uint32_t*)(g_qkv + (size_t)(ok ? kr : qrow) * QKV_);
    uint2 a = make_uint2(0u, 0u);
    if (ok) a = *(const uint2*)(p + 288 + wp);
    R.k[nt][0] = a.x; R.k[nt][1] = a.y; R.k[nt][2] = (ok && t == 0) ? p[288 + wt] : 0u;
    R.v[nt][0] = ok ? p[576 + 9 * h + t] : 0u; R.v[nt][1] = ok ? p[576 + 9 * h + 4 + t] : 0u;
    R.v[nt][2] = (ok && t == 0) ? p[576 + 9 * h + 8] : 0u;
  }
}
__device__ __noinline__ void attention(int row0, int role, int m, int aw, int lane) {
  if (lane < 8) flag_wait(&g_flags[m * 8 + lane], 1, 5);
  else if (lane < 16 && role == 0 && m > 0) flag_wait(&g_flags[(m - 1) * 8 + lane - 8], 1, 5);
  __syncwarp();
  if (aw == 0 && lane == 0) TS2(24);
  const float scale = 0.23570226039551584f;
  const int g = lane >> 2, t = lane & 3;
  const int qrow = row0 + role * 16;
  HeadRegs N;
  load_head(N, aw, qrow, g, t);
#pragma unroll 1
  for (int h = aw; h < 32; h += 8) {
    HeadRegs R = N;
    if (h + 8 < 32) load_head(N, h + 8, qrow, g, t);
    float sc[4][4];
#pragma unroll
    for (int nt = 0; nt < 4; ++nt) {
      sc[nt][0] = sc[nt][1] = sc[nt][2] = sc[nt][3] = 0.f;
      mma16816(sc[nt], R.q[0][0], R.q[1][0], R.q[0][1], R.q[1][1], R.k[nt][0], R.k[nt][1]);
      mma16816(sc[nt], R.q[0][2], R.q[1][2], 0u, 0u, R.k[nt][2], 0u);
    }
    const int par = g & 1;
    float l0[4], l1[4];
    float mx0 = -3.0e38f, mx1 = -3.0e38f;
#pragma unroll
    for (int nt = 0; nt < 4; ++nt) {
      const int jj = 8 * nt + 2 * t + par;
      const int d0 = g + 14 - jj, d1 = d0 + 8;
      const bool inr = qrow - 14 + jj >= 0;
      const bool ok0 = inr && d0 >= 0 && d0 <= 14, ok1 = inr && d1 >= 0 && d1 <= 14;
      uint32_t pk = pack_bf16(par ? sc[nt][1] : sc[nt][0], par ? sc[nt][3] : sc[nt][2]);
      pk = pack_bf16(__uint_as_float(pk << 16) * scale, __uint_as_float(pk & 0xffff0000u) * scale);
      l0[nt] = ok0 ? __uint_as_float(pk << 16) : -3.0e38f;
      l1[nt] = ok1 ? __uint_as_float(pk & 0xffff0000u) : -3.0e38f;
      mx0 = fmaxf(mx0, l0[nt]); mx1 = fmaxf(mx1, l1[nt]);
    }
    mx0 = fmaxf(mx0, __shfl_xor_sync(0xffffffffu, mx0, 1)); mx0 = fmaxf(mx0, __shfl_xor_sync(0xffffffffu, mx0, 2));
    mx1 = fmaxf(mx1, __shfl_xor_sync(0xffffffffu, mx1, 1)); mx1 = fmaxf(mx1, __shfl_xor_sync(0xffffffffu, mx1, 2));
    float s0 = 0.f, s1 = 0.f;
#pragma unroll
    for (int nt = 0; nt < 4; ++nt) {
      l0[nt] = __expf(l0[nt] - mx0); l1[nt] = __expf(l1[nt] - mx1);
      s0 += l0[nt]; s1 += l1[nt];
    }
    s0 += __shfl_xor_sync(0xffffffffu, s0, 1); s0 += __shfl_xor_sync(0xffffffffu, s0, 2);
    s1 += __shfl_xor_sync(0xffffffffu, s1, 1); s1 += __shfl_xor_sync(0xffffffffu, s1, 2);
    const float i0 = __frcp_rn(s0), i1 = __frcp_rn(s1);
    uint32_t pa[2][4];
#pragma unroll
    for (int nt = 0; nt < 4; ++nt) {
      const float p0 = l0[nt] * i0, p1 = l1[nt] * i1;
      pa[nt >> 1][(nt & 1) * 2] = par ? pack_bf16(0.f, p0) : pack_bf16(p0, 0.f);
      pa[nt >> 1][(nt & 1) * 2 + 1] = par ? pack_bf16(0.f, p1) : pack_bf16(p1, 0.f);
    }
    uint32_t* o0p = (uint32_t*)(g_act + (size_t)(qrow + g) * ACT_) + 9 * h;
    uint32_t* o1p = (uint32_t*)(g_act + (size_t)(qrow + g + 8) * ACT_) + 9 * h;
#pragma unroll
    for (int cg = 0; cg < 3; ++cg) {
      float oc[4] = {0.f, 0.f, 0.f, 0.f};
      mma16816(oc, pa[0][0], pa[0][1], pa[0][2], pa[0][3], movm(R.v[0][cg]), movm(R.v[1][cg]));
      mma16816(oc, pa[1][0], pa[1][1], pa[1][2], pa[1][3], movm(R.v[2][cg]), movm(R.v[3][cg]));
      if (cg < 2 || t == 0) {
        o0p[4 * cg + t] = pack_bf16(oc[0], oc[1]);
        o1p[4 * cg + t] = pack_bf16(oc[2], oc[3]);
      }
    }
  }
  if (aw == 0 && lane == 0) TS2(26);
}

__global__ void __cluster_dims__(2, 1, 1) __launch_bounds__(384, 1)
fused_kernel(const __grid_constant__ CUtensorMap m_qkv1, const __grid_constant__ CUtensorMap m_qkv2,
             const __grid_constant__ CUtensorMap m_gate2, const __grid_constant__ CUtensorMap m_up2,
             const __grid_constant__ CUtensorMap m_wo5, const __grid_constant__ CUtensorMap m_wo4,
             const __grid_constant__ CUtensorMap m_down5, const __grid_constant__ CUtensorMap m_down4,
             const __grid_constant__ CUtensorMap m_act,
             const __nv_bfloat16* __restrict__ x, __nv_bfloat16* __restrict__ out) {
  extern __shared__ uint8_t smem_raw[];
  const uint32_t sbase = (smem_u32(smem_raw) + 1023) & ~1023u;
  const uint32_t bars = sbase + DATA_BYTES;
  const uint32_t full1 = bars, empty1 = bars + 64, full2 = bars + 128, empty2 = bars + 192, pub = bars + 256;
  const int rank = blockIdx.x & 1, cl = blockIdx.x >> 1;
  const int role = cl & 7, m = (cl >> 3) * 2 + rank, p = role >> 1, j = role & 1;
  const int row0 = m * 128;
  const int warp = __shfl_sync(0xffffffffu, (int)(threadIdx.x >> 5), 0), lane = threadIdx.x & 31;
  const int nkb2 = (p == 3) ? 21 : 20;
  const int nblk2 = j ? 4 : 5;
  const int ncol0 = j ? 320 : 0;

  if (threadIdx.x == 0) {
    for (int s = 0; s < NS1; ++s) { mbar_init(full1 + 8 * s, 1); mbar_init(empty1 + 8 * s, MC ? 4 : 2); }
    for (int s = 0; s < NS2; ++s) { mbar_init(full2 + 8 * s, 1); mbar_init(empty2 + 8 * s, MC ? 4 : 2); }
    for (int s = 0; s < 7; ++s) mbar_init(pub + 8 * s, 256);
    asm volatile("fence.mbarrier_init.release.cluster;" ::: "memory");
  }
  __syncthreads();
  cluster_sync();

  if (warp < 4) {
    asm volatile("setmaxnreg.dec.sync.aligned.u32 40;");
    if (warp == 0) {
      if (lane == 0) {
        uint32_t it = 0;
        const int nt = num_tiles(j);
        volatile uint32_t* known = (volatile uint32_t*)(smem_raw + (bars + 320 - smem_u32(smem_raw)));
        volatile uint32_t* sched = known + 12;
        for (int t = 0; t < nt; ++t) {
          Tile T = get_tile(p, j, t);
          const CUtensorMap* mp; int cb, nmine;
          if (T.is_h) { mp = rank ? &m_up2 : &m_gate2; cb = T.col >> 6; nmine = 2; }
          else if (T.nb == 4) { mp = &m_qkv2; cb = (T.col >> 6) + 2 * rank; nmine = 2; }
          else if (T.nb == 3) { mp = rank ? &m_qkv1 : &m_qkv2; cb = (T.col >> 6) + 2 * rank; nmine = rank ? 1 : 2; }
          else { mp = &m_qkv1; cb = (T.col >> 6) + rank; nmine = 1; }
          const uint32_t doff = (T.nb == 2 ? rank : 2 * rank) * 4096;
          for (int kb = 0; kb < 18; ++kb, ++it) {
            uint32_t s = it % NS1, ph = (it / NS1) & 1;
            if (it == NS1) {
              for (int r = 0; r < 9; ++r) known[r] = 0;
              const int hlo = p == 0 ? 0 : 20 * p - 9, hhi = 20 * p + 11 + (p == 3 ? 1 : 0);
              int n = 0;
              for (int tt = 1; tt <= 5; ++tt)
                for (int hb = hlo; hb < hhi; ++hb) {
                  int TT = hb >> 1, pp = TT / 9, idx = TT - 9 * pp;
                  int ot = 1 + (idx >= 4 ? idx - 4 : idx);
                  if (ot == tt) sched[n++] = (uint32_t)hb | ((uint32_t)(2 * pp + (idx >= 4)) << 8) | ((uint32_t)(ot + 1) << 16);
                }
            }
            mbar_wait(empty1 + 8 * s, ph ^ 1, 1);
            mbar_expect_tx(full1 + 8 * s, T.nb * 4096);
            tma_load_3d_mc(sbase + RING1_OFF + s * ST1_BYTES + doff, mp, 0, kb * 32, cb, full1 + 8 * s, 3);
            (void)nmine;
          }
        }
        const CUtensorMap* mwo = j ? &m_wo4 : &m_wo5;
        const CUtensorMap* mdn = j ? &m_down4 : &m_down5;
        for (int i = 0; i < nkb2; ++i) {
          uint32_t s = i % NS2, ph = (i / NS2) & 1;
          int acol, kn, wrow; const CUtensorMap* mp; const unsigned* fl; unsigned tgt;
          if (p == 0 && i >= 11) {
            acol = (i - 11) * 64; mp = mwo; wrow = acol; fl = &g_flags[128 + m]; tgt = 8; kn = 8;
          } else {
            uint32_t e = sched[i];
            wrow = (e & 255) * 64; kn = (e >> 8) & 255; tgt = e >> 16;
            acol = 576 + wrow; mp = mdn; fl = &g_flags[m * 8 + kn];
          }
          mbar_wait(empty2 + 8 * s, ph, 2);
          mbar_expect_tx(full2 + 8 * s, 16384 + nblk2 * 8192);
          uint32_t dst = sbase + s * ST2_BYTES;
          tma_load_3d_mc(dst + 16384 + rank * nblk2 * 4096, mp, 0, wrow + 32 * rank, ncol0 >> 6, full2 + 8 * s, 3);
          if (known[kn] < tgt) { known[kn] = flag_wait(fl, tgt, 4); fence_proxy_async(); }
          tma_load_2d(dst, &m_act, acol, row0, full2 + 8 * s);
          TS2(32 + i);
        }
        agent_exit();
      }
    } else if (warp == 1) {
      const int nt = num_tiles(j);
      for (int t = 0; t < nt; ++t) {
        mbar_wait(pub + 8 * t, 0, 7);
        if (lane == 0) { if (t == 0) TS2(27); __threadfence(); flag_add(&g_flags[m * 8 + role]); if (t == 0) TS2(28); }
        __syncwarp();
        if (t == 1) {
          mbar_wait(pub + 8 * 6, 0, 7);
          if (lane == 0) { __threadfence(); flag_add(&g_flags[128 + m]); }
          __syncwarp();
        }
      }
      if (lane == 0) agent_exit();
    }
  } else {
    asm volatile("setmaxnreg.inc.sync.aligned.u32 232;");
    Ctx c;
    c.sbase = sbase; c.full1 = full1; c.empty1 = empty1; c.full2 = full2; c.empty2 = empty2; c.peer = rank ^ 1;
    c.wg = (warp - 4) >> 2; c.tid = threadIdx.x - 128 - c.wg * 128;
    const int w = c.tid >> 5;
    if (c.wg == 0 && c.tid == 0) TS(0);
    {
      const int sub = lane >> 3, li = lane & 7;
      uint4 nx[9];
      {
        const uint4* src = (const uint4*)(x + (size_t)(row0 + c.wg * 64 + w * 16 + sub) * D_) + li;
#pragma unroll
        for (int t = 0; t < 9; ++t) nx[t] = __ldg(src + 8 * t);
      }
#pragma unroll 1
      for (int itr = 0; itr < 4; ++itr) {
        const int r = c.wg * 64 + w * 16 + itr * 4 + sub;
        uint4 xv[9];
#pragma unroll
        for (int t = 0; t < 9; ++t) xv[t] = nx[t];
        if (itr < 3) {
          const uint4* src = (const uint4*)(x + (size_t)(row0 + r + 4) * D_) + li;
#pragma unroll
          for (int t = 0; t < 9; ++t) nx[t] = __ldg(src + 8 * t);
        }
        float s0 = 0.f, s1 = 0.f;
#pragma unroll
        for (int t = 0; t < 9; ++t) {
          const uint32_t* u = (const uint32_t*)&xv[t];
#pragma unroll
          for (int e = 0; e < 4; ++e) { s0 += __uint_as_float(u[e] << 16); s1 += __uint_as_float(u[e] & 0xffff0000u); }
        }
        float sum = s0 + s1;
        sum += __shfl_xor_sync(0xffffffffu, sum, 1); sum += __shfl_xor_sync(0xffffffffu, sum, 2); sum += __shfl_xor_sync(0xffffffffu, sum, 4);
        const float mean = sum * (1.f / 576.f);
        float q0 = 0.f, q1 = 0.f;
#pragma unroll
        for (int t = 0; t < 9; ++t) {
          const uint32_t* u = (const uint32_t*)&xv[t];
#pragma unroll
          for (int e = 0; e < 4; ++e) {
            float a = __uint_as_float(u[e] << 16) - mean, b = __uint_as_float(u[e] & 0xffff0000u) - mean;
            q0 = fmaf(a, a, q0); q1 = fmaf(b, b, q1);
          }
        }
        float sq = q0 + q1;
        sq += __shfl_xor_sync(0xffffffffu, sq, 1); sq += __shfl_xor_sync(0xffffffffu, sq, 2); sq += __shfl_xor_sync(0xffffffffu, sq, 4);
        const float vb = bf16r(sq * (1.f / 576.f));
        const float rinv = 1.f / bf16r(sqrtf(bf16r(vb + 1e-5f)));
        const __nv_bfloat162 mb2 = __float2bfloat162_rn(mean);
        const uint32_t dsta = sbase + r * 128 + ((li ^ (r & 7)) << 4);
#pragma unroll
        for (int t = 0; t < 9; ++t) {
          const uint32_t* u = (const uint32_t*)&xv[t];
          uint32_t o[4];
#pragma unroll
          for (int e = 0; e < 4; ++e) {
            __nv_bfloat162 d2 = __hsub2(*(const __nv_bfloat162*)&u[e], mb2);
            uint32_t du = *(uint32_t*)&d2;
            o[e] = pack_bf16(__uint_as_float(du << 16) * rinv, __uint_as_float(du & 0xffff0000u) * rinv);
          }
          asm volatile("st.shared.v4.b32 [%0], {%1, %2, %3, %4};" ::"r"(dsta + t * 16384), "r"(o[0]), "r"(o[1]), "r"(o[2]), "r"(o[3]) : "memory");
        }
      }
      asm volatile("fence.proxy.async.shared::cta;" ::: "memory");
      named_bar(1 + c.wg, 128);
    }
    if (c.wg == 0 && c.tid == 0) TS(1);
    unsigned* myflag = &g_flags[m * 8 + role];
    {
      uint32_t it = 0;
      const int nt = num_tiles(j);
#pragma unroll 1
      for (int t = 0; t < nt; ++t) {
        Tile T = get_tile(p, j, t);
        unsigned* pend = t ? myflag : nullptr;
        if (T.nb == 4) {
          float acc[128] = {};
          g1_tile<4>(c, acc, it, pend);
          if (T.is_h) epi_h<4>(c, acc, row0, T.col); else epi_qkv<4>(c, acc, row0, T.col);
        } else if (T.nb == 3) {
          float acc[96] = {};
          g1_tile<3>(c, acc, it, pend);
          epi_qkv<3>(c, acc, row0, T.col);
        } else {
          float acc[64] = {};
          g1_tile<2>(c, acc, it, pend);
          epi_qkv<2>(c, acc, row0, T.col);
        }
        if (t == nt - 1 && c.tid == 0) {
          for (int s = 0; s < NS2; ++s) { mbar_arrive_both(empty2 + 8 * s); }
        }
        mbar_arrive_local(pub + 8 * t);
        if (t == 1) {
          if (c.wg == 0 && c.tid == 0) TS(11);
          attention(row0, role, m, c.wg * 4 + w, lane);
          mbar_arrive_local(pub + 8 * 6);
          if (c.wg == 0 && c.tid == 0) TS(12);
        }
        if (c.wg == 0 && c.tid == 0) TS(2 + t);
      }
    }
    const int nch = j ? 32 : 40;
    const uint32_t pitch = nch * 32 + 32;
    const uint32_t sacc = sbase + (c.wg * 64 + w * 16 + (lane >> 2)) * pitch + (lane & 3) * 8;
    if (j == 0) {
      float acc1[96] = {}, acc2[64] = {};
      wgmma_fence();
#pragma unroll 1
      for (int i = 0; i < nkb2; ++i) {
        uint32_t s = i % NS2, ph = (i / NS2) & 1;
        mbar_wait(full2 + 8 * s, ph, 3);
        if (c.wg == 0 && c.tid == 0) TS2(i);
        uint32_t a0 = sbase + s * ST2_BYTES + c.wg * 8192, b0 = sbase + s * ST2_BYTES + 16384;
#pragma unroll
        for (int k = 0; k < 4; ++k) {
          uint64_t da = make_desc(a0 + k * 32, 16, 1024);
          const uint32_t bk = b0 + (k >> 1) * (5 * 4096) + (k & 1) * 2048;
          wgmma_n192(acc1, da, make_desc(bk, 4096, 1024), (i | k) != 0);
          wgmma_n128(acc2, da, make_desc(bk + 3 * 4096, 4096, 1024), (i | k) != 0);
        }
        wgmma_commit();
        if (i > 0) {
          wgmma_wait<1>();
          if (c.tid == 0 && i - 1 + NS2 < nkb2) { uint32_t sp = (i - 1) % NS2; mbar_arrive_both(empty2 + 8 * sp); }
        }
      }
      wgmma_wait<0>();
      if (c.wg == 0 && c.tid == 0) TS(8);
      named_bar(3, 256);
      acc_to_smem<96>(acc1, sacc, pitch);
      acc_to_smem<64>(acc2, sacc + 768, pitch);
    } else {
      float acc[128] = {};
      wgmma_fence();
#pragma unroll 1
      for (int i = 0; i < nkb2; ++i) {
        uint32_t s = i % NS2, ph = (i / NS2) & 1;
        mbar_wait(full2 + 8 * s, ph, 3);
        if (c.wg == 0 && c.tid == 0) TS2(i);
        uint32_t a0 = sbase + s * ST2_BYTES + c.wg * 8192, b0 = sbase + s * ST2_BYTES + 16384;
#pragma unroll
        for (int k = 0; k < 4; ++k)
          wgmma_n256(acc, make_desc(a0 + k * 32, 16, 1024), make_desc(b0 + (k >> 1) * (4 * 4096) + (k & 1) * 2048, 4096, 1024), (i | k) != 0);
        wgmma_commit();
        if (i > 0) {
          wgmma_wait<1>();
          if (c.tid == 0 && i - 1 + NS2 < nkb2) { uint32_t sp = (i - 1) % NS2; mbar_arrive_both(empty2 + 8 * sp); }
        }
      }
      wgmma_wait<0>();
      if (c.wg == 0 && c.tid == 0) TS(8);
      named_bar(3, 256);
      acc_to_smem<128>(acc, sacc, pitch);
    }
    named_bar(3, 256);
    {
      const int t256 = c.wg * 128 + c.tid;
      uint4* xs = g_xch + (size_t)((m * 2 + j) * 4) * 128 * 40;
      unsigned* pf = &g_flags[144 + (m * 2 + j) * 4];
#pragma unroll 1
      for (int e = t256; e < 96 * nch; e += 256) {
        int r = e / nch, cI = e - r * nch;
        r += (r >= 32 * p) ? 32 : 0;
        float4 u0 = lds128(sbase + r * pitch + cI * 32), u1 = lds128(sbase + r * pitch + cI * 32 + 16);
        xs[((size_t)p * 128 + r) * 40 + cI] = make_uint4(pack_bf16(u0.x, u0.y), pack_bf16(u0.z, u0.w), pack_bf16(u1.x, u1.y), pack_bf16(u1.z, u1.w));
      }
      named_bar(3, 256);
      if (t256 == 0) {
        __threadfence();
        for (int q = 0; q < 4; ++q) if (q != p) flag_add(pf + q);
      }
      if (lane == 0) flag_wait(pf + p, 3, 6);
      __syncwarp();
      if (c.wg == 0 && c.tid == 0) TS(9);
      const int nit = nch >> 3;
#pragma unroll
      for (int i = 0; i < 5; ++i) {
        if (i < nit) {
          const int e = t256 + i * 256;
          const int rl = e / nch, cI = e - rl * nch, r = 32 * p + rl;
          uint4 v[3];
#pragma unroll
          for (int k = 0; k < 3; ++k) v[k] = __ldcg(xs + ((size_t)(k + (k >= p)) * 128 + r) * 40 + cI);
          const size_t off = (size_t)(row0 + r) * D_ + ncol0 + cI * 8;
          const uint4 xv = __ldg((const uint4*)(x + off));
          float4 u0 = lds128(sbase + r * pitch + cI * 32), u1 = lds128(sbase + r * pitch + cI * 32 + 16);
          float f[8] = {u0.x, u0.y, u0.z, u0.w, u1.x, u1.y, u1.z, u1.w};
          uint32_t o[4];
#pragma unroll
          for (int e2 = 0; e2 < 4; ++e2) {
            const uint32_t w0 = ((const uint32_t*)&v[0])[e2], w1 = ((const uint32_t*)&v[1])[e2], w2 = ((const uint32_t*)&v[2])[e2], w3 = ((const uint32_t*)&xv)[e2];
            float lo = f[2 * e2] + ((__uint_as_float(w0 << 16) + __uint_as_float(w1 << 16)) + (__uint_as_float(w2 << 16) + __uint_as_float(w3 << 16)));
            float hi = f[2 * e2 + 1] + ((__uint_as_float(w0 & 0xffff0000u) + __uint_as_float(w1 & 0xffff0000u)) + (__uint_as_float(w2 & 0xffff0000u) + __uint_as_float(w3 & 0xffff0000u)));
            o[e2] = pack_bf16(lo, hi);
          }
          *(uint4*)(out + off) = make_uint4(o[0], o[1], o[2], o[3]);
        }
      }
      if (c.wg == 0 && c.tid == 0) TS(10);
    }
    named_bar(1 + c.wg, 128);
    if (c.tid == 0) agent_exit();
  }
}

typedef CUresult (*EncodeFn)(CUtensorMap*, CUtensorMapDataType, cuuint32_t, void*, const cuuint64_t*, const cuuint64_t*,
                             const cuuint32_t*, const cuuint32_t*, CUtensorMapInterleave, CUtensorMapSwizzle,
                             CUtensorMapL2promotion, CUtensorMapFloatOOBfill);

static void make_map2(EncodeFn enc, CUtensorMap* mp, const void* ptr, int rows, int cols, int box_rows) {
  cuuint64_t dims[2] = {(cuuint64_t)cols, (cuuint64_t)rows};
  cuuint64_t strides[1] = {(cuuint64_t)cols * 2};
  cuuint32_t box[2] = {64, (cuuint32_t)box_rows};
  cuuint32_t es[2] = {1, 1};
  enc(mp, CU_TENSOR_MAP_DATA_TYPE_BFLOAT16, 2, (void*)ptr, dims, strides, box, es, CU_TENSOR_MAP_INTERLEAVE_NONE,
      CU_TENSOR_MAP_SWIZZLE_128B, CU_TENSOR_MAP_L2_PROMOTION_L2_256B, CU_TENSOR_MAP_FLOAT_OOB_FILL_NONE);
}
static void make_map3(EncodeFn enc, CUtensorMap* mp, const void* ptr, int rows, int cols, int nblk) {
  cuuint64_t dims[3] = {64, (cuuint64_t)rows, (cuuint64_t)(cols / 64)};
  cuuint64_t strides[2] = {(cuuint64_t)cols * 2, 128};
  cuuint32_t box[3] = {64, 32, (cuuint32_t)nblk};
  cuuint32_t es[3] = {1, 1, 1};
  enc(mp, CU_TENSOR_MAP_DATA_TYPE_BFLOAT16, 3, (void*)ptr, dims, strides, box, es, CU_TENSOR_MAP_INTERLEAVE_NONE,
      CU_TENSOR_MAP_SWIZZLE_128B, CU_TENSOR_MAP_L2_PROMOTION_L2_256B, CU_TENSOR_MAP_FLOAT_OOB_FILL_NONE);
}

extern "C" void kernel_launch(void* const* d_in, const int* in_sizes, int n_in, void* d_out, int out_size) {
  static EncodeFn enc = nullptr;
  static void* act_ptr = nullptr;
  if (!enc) {
    void* fn = nullptr;
    cudaDriverEntryPointQueryResult qr;
    cudaGetDriverEntryPoint("cuTensorMapEncodeTiled", &fn, cudaEnableDefault, &qr);
    enc = (EncodeFn)fn;
    cudaGetSymbolAddress(&act_ptr, g_act);
    cudaFuncSetAttribute(fused_kernel, cudaFuncAttributeMaxDynamicSharedMemorySize, SMEM_BYTES);
  }
  const __nv_bfloat16* x = (const __nv_bfloat16*)d_in[0];
  CUtensorMap m_qkv1, m_qkv2, m_gate2, m_up2, m_wo5, m_wo4, m_down5, m_down4, m_act;
  make_map3(enc, &m_qkv1, d_in[1], D_, QKV_, 1);
  make_map3(enc, &m_qkv2, d_in[1], D_, QKV_, 2);
  make_map3(enc, &m_gate2, d_in[4], D_, F_, 2);
  make_map3(enc, &m_up2, d_in[5], D_, F_, 2);
  make_map3(enc, &m_wo5, d_in[2], D_, D_, 5);
  make_map3(enc, &m_wo4, d_in[2], D_, D_, 4);
  make_map3(enc, &m_down5, d_in[6], F_, D_, 5);
  make_map3(enc, &m_down4, d_in[6], F_, D_, 4);
  make_map2(enc, &m_act, act_ptr, S_, ACT_, 128);
  fused_kernel<<<128, 384, SMEM_BYTES>>>(m_qkv1, m_qkv2, m_gate2, m_up2, m_wo5, m_wo4, m_down5, m_down4, m_act, x, (__nv_bfloat16*)d_out);
}
```

```cpp
#include <cuda_runtime.h>
#include <cuda_bf16.h>
#include <cuda.h>
#include <stdint.h>

constexpr int S_ = 2048, D_ = 576, F_ = 4608, QKV_ = 1728, ACT_ = 5184;
constexpr int NS1 = 7;
constexpr int NS2 = 4;
constexpr int XN_BYTES = 9 * 16384;
constexpr int RING1_OFF = 7 * 16384;
__device__ __forceinline__ uint32_t slot1_off(uint32_t s) { return RING1_OFF + (s >= 5 ? s - 5 : s + 2) * 16384; }
constexpr int ST1_BYTES = 16384;
constexpr int ST2_BYTES = 57344;
constexpr int DATA_BYTES = 229376;
constexpr int SMEM_BYTES = DATA_BYTES + 1024 + 512;
constexpr int NAGENTS = 128 * 4;
#define SKEW 0
#define MC 1

__device__ __align__(1024) __nv_bfloat16 g_qkv[S_ * QKV_];
__device__ __align__(1024) __nv_bfloat16 g_act[S_ * ACT_];
__device__ __align__(1024) uint4 g_xch[16 * 2 * 4 * 128 * 40];
__device__ unsigned int g_flags[288];
#define TS(i)
#define TS2(i)
#define FAIL(code) __trap()
#define SPIN_MAX (1u << 24)

__device__ __forceinline__ void wgmma_n128(float (&d)[64], uint64_t da, uint64_t db, int scale_d) {
  asm volatile("{\n.reg .pred p;\nsetp.ne.b32 p, %66, 0;\n"
    "wgmma.mma_async.sync.aligned.m64n128k16.f32.bf16.bf16 {%0, %1, %2, %3, %4, %5, %6, %7, %8, %9, %10, %11, %12, %13, %14, %15, %16, %17, %18, %19, %20, %21, %22, %23, %24, %25, %26, %27, %28, %29, %30, %31, %32, %33, %34, %35, %36, %37, %38, %39, %40, %41, %42, %43, %44, %45, %46, %47, %48, %49, %50, %51, %52, %53, %54, %55, %56, %57, %58, %59, %60, %61, %62, %63}, %64, %65, p, 1, 1, 0, 1;\n}\n"
    : "+f"(d[0]), "+f"(d[1]), "+f"(d[2]), "+f"(d[3]), "+f"(d[4]), "+f"(d[5]), "+f"(d[6]), "+f"(d[7]), "+f"(d[8]), "+f"(d[9]), "+f"(d[10]), "+f"(d[11]), "+f"(d[12]), "+f"(d[13]), "+f"(d[14]), "+f"(d[15]), "+f"(d[16]), "+f"(d[17]), "+f"(d[18]), "+f"(d[19]), "+f"(d[20]), "+f"(d[21]), "+f"(d[22]), "+f"(d[23]), "+f"(d[24]), "+f"(d[25]), "+f"(d[26]), "+f"(d[27]), "+f"(d[28]), "+f"(d[29]), "+f"(d[30]), "+f"(d[31]), "+f"(d[32]), "+f"(d[33]), "+f"(d[34]), "+f"(d[35]), "+f"(d[36]), "+f"(d[37]), "+f"(d[38]), "+f"(d[39]), "+f"(d[40]), "+f"(d[41]), "+f"(d[42]), "+f"(d[43]), "+f"(d[44]), "+f"(d[45]), "+f"(d[46]), "+f"(d[47]), "+f"(d[48]), "+f"(d[49]), "+f"(d[50]), "+f"(d[51]), "+f"(d[52]), "+f"(d[53]), "+f"(d[54]), "+f"(d[55]), "+f"(d[56]), "+f"(d[57]), "+f"(d[58]), "+f"(d[59]), "+f"(d[60]), "+f"(d[61]), "+f"(d[62]), "+f"(d[63])
    : "l"(da), "l"(db), "r"(scale_d));
}

__device__ __forceinline__ void wgmma_n192(float (&d)[96], uint64_t da, uint64_t db, int scale_d) {
  asm volatile("{\n.reg .pred p;\nsetp.ne.b32 p, %98, 0;\n"
    "wgmma.mma_async.sync.aligned.m64n192k16.f32.bf16.bf16 {%0, %1, %2, %3, %4, %5, %6, %7, %8, %9, %10, %11, %12, %13, %14, %15, %16, %17, %18, %19, %20, %21, %22, %23, %24, %25, %26, %27, %28, %29, %30, %31, %32, %33, %34, %35, %36, %37, %38, %39, %40, %41, %42, %43, %44, %45, %46, %47, %48, %49, %50, %51, %52, %53, %54, %55, %56, %57, %58, %59, %60, %61, %62, %63, %64, %65, %66, %67, %68, %69, %70, %71, %72, %73, %74, %75, %76, %77, %78, %79, %80, %81, %82, %83, %84, %85, %86, %87, %88, %89, %90, %91, %92, %93, %94, %95}, %96, %97, p, 1, 1, 0, 1;\n}\n"
    : "+f"(d[0]), "+f"(d[1]), "+f"(d[2]), "+f"(d[3]), "+f"(d[4]), "+f"(d[5]), "+f"(d[6]), "+f"(d[7]), "+f"(d[8]), "+f"(d[9]), "+f"(d[10]), "+f"(d[11]), "+f"(d[12]), "+f"(d[13]), "+f"(d[14]), "+f"(d[15]), "+f"(d[16]), "+f"(d[17]), "+f"(d[18]), "+f"(d[19]), "+f"(d[20]), "+f"(d[21]), "+f"(d[22]), "+f"(d[23]), "+f"(d[24]), "+f"(d[25]), "+f"(d[26]), "+f"(d[27]), "+f"(d[28]), "+f"(d[29]), "+f"(d[30]), "+f"(d[31]), "+f"(d[32]), "+f"(d[33]), "+f"(d[34]), "+f"(d[35]), "+f"(d[36]), "+f"(d[37]), "+f"(d[38]), "+f"(d[39]), "+f"(d[40]), "+f"(d[41]), "+f"(d[42]), "+f"(d[43]), "+f"(d[44]), "+f"(d[45]), "+f"(d[46]), "+f"(d[47]), "+f"(d[48]), "+f"(d[49]), "+f"(d[50]), "+f"(d[51]), "+f"(d[52]), "+f"(d[53]), "+f"(d[54]), "+f"(d[55]), "+f"(d[56]), "+f"(d[57]), "+f"(d[58]), "+f"(d[59]), "+f"(d[60]), "+f"(d[61]), "+f"(d[62]), "+f"(d[63]), "+f"(d[64]), "+f"(d[65]), "+f"(d[66]), "+f"(d[67]), "+f"(d[68]), "+f"(d[69]), "+f"(d[70]), "+f"(d[71]), "+f"(d[72]), "+f"(d[73]), "+f"(d[74]), "+f"(d[75]), "+f"(d[76]), "+f"(d[77]), "+f"(d[78]), "+f"(d[79]), "+f"(d[80]), "+f"(d[81]), "+f"(d[82]), "+f"(d[83]), "+f"(d[84]), "+f"(d[85]), "+f"(d[86]), "+f"(d[87]), "+f"(d[88]), "+f"(d[89]), "+f"(d[90]), "+f"(d[91]), "+f"(d[92]), "+f"(d[93]), "+f"(d[94]), "+f"(d[95])
    : "l"(da), "l"(db), "r"(scale_d));
}

__device__ __forceinline__ void wgmma_n256(float (&d)[128], uint64_t da, uint64_t db, int scale_d) {
  asm volatile("{\n.reg .pred p;\nsetp.ne.b32 p, %130, 0;\n"
    "wgmma.mma_async.sync.aligned.m64n256k16.f32.bf16.bf16 {%0, %1, %2, %3, %4, %5, %6, %7, %8, %9, %10, %11, %12, %13, %14, %15, %16, %17, %18, %19, %20, %21, %22, %23, %24, %25, %26, %27, %28, %29, %30, %31, %32, %33, %34, %35, %36, %37, %38, %39, %40, %41, %42, %43, %44, %45, %46, %47, %48, %49, %50, %51, %52, %53, %54, %55, %56, %57, %58, %59, %60, %61, %62, %63, %64, %65, %66, %67, %68, %69, %70, %71, %72, %73, %74, %75, %76, %77, %78, %79, %80, %81, %82, %83, %84, %85, %86, %87, %88, %89, %90, %91, %92, %93, %94, %95, %96, %97, %98, %99, %100, %101, %102, %103, %104, %105, %106, %107, %108, %109, %110, %111, %112, %113, %114, %115, %116, %117, %118, %119, %120, %121, %122, %123, %124, %125, %126, %127}, %128, %129, p, 1, 1, 0, 1;\n}\n"
    : "+f"(d[0]), "+f"(d[1]), "+f"(d[2]), "+f"(d[3]), "+f"(d[4]), "+f"(d[5]), "+f"(d[6]), "+f"(d[7]), "+f"(d[8]), "+f"(d[9]), "+f"(d[10]), "+f"(d[11]), "+f"(d[12]), "+f"(d[13]), "+f"(d[14]), "+f"(d[15]), "+f"(d[16]), "+f"(d[17]), "+f"(d[18]), "+f"(d[19]), "+f"(d[20]), "+f"(d[21]), "+f"(d[22]), "+f"(d[23]), "+f"(d[24]), "+f"(d[25]), "+f"(d[26]), "+f"(d[27]), "+f"(d[28]), "+f"(d[29]), "+f"(d[30]), "+f"(d[31]), "+f"(d[32]), "+f"(d[33]), "+f"(d[34]), "+f"(d[35]), "+f"(d[36]), "+f"(d[37]), "+f"(d[38]), "+f"(d[39]), "+f"(d[40]), "+f"(d[41]), "+f"(d[42]), "+f"(d[43]), "+f"(d[44]), "+f"(d[45]), "+f"(d[46]), "+f"(d[47]), "+f"(d[48]), "+f"(d[49]), "+f"(d[50]), "+f"(d[51]), "+f"(d[52]), "+f"(d[53]), "+f"(d[54]), "+f"(d[55]), "+f"(d[56]), "+f"(d[57]), "+f"(d[58]), "+f"(d[59]), "+f"(d[60]), "+f"(d[61]), "+f"(d[62]), "+f"(d[63]), "+f"(d[64]), "+f"(d[65]), "+f"(d[66]), "+f"(d[67]), "+f"(d[68]), "+f"(d[69]), "+f"(d[70]), "+f"(d[71]), "+f"(d[72]), "+f"(d[73]), "+f"(d[74]), "+f"(d[75]), "+f"(d[76]), "+f"(d[77]), "+f"(d[78]), "+f"(d[79]), "+f"(d[80]), "+f"(d[81]), "+f"(d[82]), "+f"(d[83]), "+f"(d[84]), "+f"(d[85]), "+f"(d[86]), "+f"(d[87]), "+f"(d[88]), "+f"(d[89]), "+f"(d[90]), "+f"(d[91]), "+f"(d[92]), "+f"(d[93]), "+f"(d[94]), "+f"(d[95]), "+f"(d[96]), "+f"(d[97]), "+f"(d[98]), "+f"(d[99]), "+f"(d[100]), "+f"(d[101]), "+f"(d[102]), "+f"(d[103]), "+f"(d[104]), "+f"(d[105]), "+f"(d[106]), "+f"(d[107]), "+f"(d[108]), "+f"(d[109]), "+f"(d[110]), "+f"(d[111]), "+f"(d[112]), "+f"(d[113]), "+f"(d[114]), "+f"(d[115]), "+f"(d[116]), "+f"(d[117]), "+f"(d[118]), "+f"(d[119]), "+f"(d[120]), "+f"(d[121]), "+f"(d[122]), "+f"(d[123]), "+f"(d[124]), "+f"(d[125]), "+f"(d[126]), "+f"(d[127])
    : "l"(da), "l"(db), "r"(scale_d));
}

__device__ __forceinline__ void wgmma_rs_n128(float (&d)[64], const uint32_t (&a)[4], uint64_t db) {
  asm volatile(
    "wgmma.mma_async.sync.aligned.m64n128k16.f32.bf16.bf16 {%0, %1, %2, %3, %4, %5, %6, %7, %8, %9, %10, %11, %12, %13, %14, %15, %16, %17, %18, %19, %20, %21, %22, %23, %24, %25, %26, %27, %28, %29, %30, %31, %32, %33, %34, %35, %36, %37, %38, %39, %40, %41, %42, %43, %44, %45, %46, %47, %48, %49, %50, %51, %52, %53, %54, %55, %56, %57, %58, %59, %60, %61, %62, %63}, {%64, %65, %66, %67}, %68, 1, 1, 1, 1;\n"
    : "+f"(d[0]), "+f"(d[1]), "+f"(d[2]), "+f"(d[3]), "+f"(d[4]), "+f"(d[5]), "+f"(d[6]), "+f"(d[7]), "+f"(d[8]), "+f"(d[9]), "+f"(d[10]), "+f"(d[11]), "+f"(d[12]), "+f"(d[13]), "+f"(d[14]), "+f"(d[15]), "+f"(d[16]), "+f"(d[17]), "+f"(d[18]), "+f"(d[19]), "+f"(d[20]), "+f"(d[21]), "+f"(d[22]), "+f"(d[23]), "+f"(d[24]), "+f"(d[25]), "+f"(d[26]), "+f"(d[27]), "+f"(d[28]), "+f"(d[29]), "+f"(d[30]), "+f"(d[31]), "+f"(d[32]), "+f"(d[33]), "+f"(d[34]), "+f"(d[35]), "+f"(d[36]), "+f"(d[37]), "+f"(d[38]), "+f"(d[39]), "+f"(d[40]), "+f"(d[41]), "+f"(d[42]), "+f"(d[43]), "+f"(d[44]), "+f"(d[45]), "+f"(d[46]), "+f"(d[47]), "+f"(d[48]), "+f"(d[49]), "+f"(d[50]), "+f"(d[51]), "+f"(d[52]), "+f"(d[53]), "+f"(d[54]), "+f"(d[55]), "+f"(d[56]), "+f"(d[57]), "+f"(d[58]), "+f"(d[59]), "+f"(d[60]), "+f"(d[61]), "+f"(d[62]), "+f"(d[63])
    : "r"(a[0]), "r"(a[1]), "r"(a[2]), "r"(a[3]), "l"(db));
}

__device__ __forceinline__ void wgmma_rs_n192(float (&d)[96], const uint32_t (&a)[4], uint64_t db) {
  asm volatile(
    "wgmma.mma_async.sync.aligned.m64n192k16.f32.bf16.bf16 {%0, %1, %2, %3, %4, %5, %6, %7, %8, %9, %10, %11, %12, %13, %14, %15, %16, %17, %18, %19, %20, %21, %22, %23, %24, %25, %26, %27, %28, %29, %30, %31, %32, %33, %34, %35, %36, %37, %38, %39, %40, %41, %42, %43, %44, %45, %46, %47, %48, %49, %50, %51, %52, %53, %54, %55, %56, %57, %58, %59, %60, %61, %62, %63, %64, %65, %66, %67, %68, %69, %70, %71, %72, %73, %74, %75, %76, %77, %78, %79, %80, %81, %82, %83, %84, %85, %86, %87, %88, %89, %90, %91, %92, %93, %94, %95}, {%96, %97, %98, %99}, %100, 1, 1, 1, 1;\n"
    : "+f"(d[0]), "+f"(d[1]), "+f"(d[2]), "+f"(d[3]), "+f"(d[4]), "+f"(d[5]), "+f"(d[6]), "+f"(d[7]), "+f"(d[8]), "+f"(d[9]), "+f"(d[10]), "+f"(d[11]), "+f"(d[12]), "+f"(d[13]), "+f"(d[14]), "+f"(d[15]), "+f"(d[16]), "+f"(d[17]), "+f"(d[18]), "+f"(d[19]), "+f"(d[20]), "+f"(d[21]), "+f"(d[22]), "+f"(d[23]), "+f"(d[24]), "+f"(d[25]), "+f"(d[26]), "+f"(d[27]), "+f"(d[28]), "+f"(d[29]), "+f"(d[30]), "+f"(d[31]), "+f"(d[32]), "+f"(d[33]), "+f"(d[34]), "+f"(d[35]), "+f"(d[36]), "+f"(d[37]), "+f"(d[38]), "+f"(d[39]), "+f"(d[40]), "+f"(d[41]), "+f"(d[42]), "+f"(d[43]), "+f"(d[44]), "+f"(d[45]), "+f"(d[46]), "+f"(d[47]), "+f"(d[48]), "+f"(d[49]), "+f"(d[50]), "+f"(d[51]), "+f"(d[52]), "+f"(d[53]), "+f"(d[54]), "+f"(d[55]), "+f"(d[56]), "+f"(d[57]), "+f"(d[58]), "+f"(d[59]), "+f"(d[60]), "+f"(d[61]), "+f"(d[62]), "+f"(d[63]), "+f"(d[64]), "+f"(d[65]), "+f"(d[66]), "+f"(d[67]), "+f"(d[68]), "+f"(d[69]), "+f"(d[70]), "+f"(d[71]), "+f"(d[72]), "+f"(d[73]), "+f"(d[74]), "+f"(d[75]), "+f"(d[76]), "+f"(d[77]), "+f"(d[78]), "+f"(d[79]), "+f"(d[80]), "+f"(d[81]), "+f"(d[82]), "+f"(d[83]), "+f"(d[84]), "+f"(d[85]), "+f"(d[86]), "+f"(d[87]), "+f"(d[88]), "+f"(d[89]), "+f"(d[90]), "+f"(d[91]), "+f"(d[92]), "+f"(d[93]), "+f"(d[94]), "+f"(d[95])
    : "r"(a[0]), "r"(a[1]), "r"(a[2]), "r"(a[3]), "l"(db));
}

__device__ __forceinline__ void wgmma_rs_n256(float (&d)[128], const uint32_t (&a)[4], uint64_t db) {
  asm volatile(
    "wgmma.mma_async.sync.aligned.m64n256k16.f32.bf16.bf16 {%0, %1, %2, %3, %4, %5, %6, %7, %8, %9, %10, %11, %12, %13, %14, %15, %16, %17, %18, %19, %20, %21, %22, %23, %24, %25, %26, %27, %28, %29, %30, %31, %32, %33, %34, %35, %36, %37, %38, %39, %40, %41, %42, %43, %44, %45, %46, %47, %48, %49, %50, %51, %52, %53, %54, %55, %56, %57, %58, %59, %60, %61, %62, %63, %64, %65, %66, %67, %68, %69, %70, %71, %72, %73, %74, %75, %76, %77, %78, %79, %80, %81, %82, %83, %84, %85, %86, %87, %88, %89, %90, %91, %92, %93, %94, %95, %96, %97, %98, %99, %100, %101, %102, %103, %104, %105, %106, %107, %108, %109, %110, %111, %112, %113, %114, %115, %116, %117, %118, %119, %120, %121, %122, %123, %124, %125, %126, %127}, {%128, %129, %130, %131}, %132, 1, 1, 1, 1;\n"
    : "+f"(d[0]), "+f"(d[1]), "+f"(d[2]), "+f"(d[3]), "+f"(d[4]), "+f"(d[5]), "+f"(d[6]), "+f"(d[7]), "+f"(d[8]), "+f"(d[9]), "+f"(d[10]), "+f"(d[11]), "+f"(d[12]), "+f"(d[13]), "+f"(d[14]), "+f"(d[15]), "+f"(d[16]), "+f"(d[17]), "+f"(d[18]), "+f"(d[19]), "+f"(d[20]), "+f"(d[21]), "+f"(d[22]), "+f"(d[23]), "+f"(d[24]), "+f"(d[25]), "+f"(d[26]), "+f"(d[27]), "+f"(d[28]), "+f"(d[29]), "+f"(d[30]), "+f"(d[31]), "+f"(d[32]), "+f"(d[33]), "+f"(d[34]), "+f"(d[35]), "+f"(d[36]), "+f"(d[37]), "+f"(d[38]), "+f"(d[39]), "+f"(d[40]), "+f"(d[41]), "+f"(d[42]), "+f"(d[43]), "+f"(d[44]), "+f"(d[45]), "+f"(d[46]), "+f"(d[47]), "+f"(d[48]), "+f"(d[49]), "+f"(d[50]), "+f"(d[51]), "+f"(d[52]), "+f"(d[53]), "+f"(d[54]), "+f"(d[55]), "+f"(d[56]), "+f"(d[57]), "+f"(d[58]), "+f"(d[59]), "+f"(d[60]), "+f"(d[61]), "+f"(d[62]), "+f"(d[63]), "+f"(d[64]), "+f"(d[65]), "+f"(d[66]), "+f"(d[67]), "+f"(d[68]), "+f"(d[69]), "+f"(d[70]), "+f"(d[71]), "+f"(d[72]), "+f"(d[73]), "+f"(d[74]), "+f"(d[75]), "+f"(d[76]), "+f"(d[77]), "+f"(d[78]), "+f"(d[79]), "+f"(d[80]), "+f"(d[81]), "+f"(d[82]), "+f"(d[83]), "+f"(d[84]), "+f"(d[85]), "+f"(d[86]), "+f"(d[87]), "+f"(d[88]), "+f"(d[89]), "+f"(d[90]), "+f"(d[91]), "+f"(d[92]), "+f"(d[93]), "+f"(d[94]), "+f"(d[95]), "+f"(d[96]), "+f"(d[97]), "+f"(d[98]), "+f"(d[99]), "+f"(d[100]), "+f"(d[101]), "+f"(d[102]), "+f"(d[103]), "+f"(d[104]), "+f"(d[105]), "+f"(d[106]), "+f"(d[107]), "+f"(d[108]), "+f"(d[109]), "+f"(d[110]), "+f"(d[111]), "+f"(d[112]), "+f"(d[113]), "+f"(d[114]), "+f"(d[115]), "+f"(d[116]), "+f"(d[117]), "+f"(d[118]), "+f"(d[119]), "+f"(d[120]), "+f"(d[121]), "+f"(d[122]), "+f"(d[123]), "+f"(d[124]), "+f"(d[125]), "+f"(d[126]), "+f"(d[127])
    : "r"(a[0]), "r"(a[1]), "r"(a[2]), "r"(a[3]), "l"(db));
}

__device__ __forceinline__ uint32_t smem_u32(const void* p) { return (uint32_t)__cvta_generic_to_shared(p); }
__device__ __forceinline__ void mbar_init(uint32_t a, uint32_t cnt) { asm volatile("mbarrier.init.shared::cta.b64 [%0], %1;" ::"r"(a), "r"(cnt)); }
__device__ __forceinline__ void mbar_expect_tx(uint32_t a, uint32_t bytes) {
  asm volatile("mbarrier.arrive.expect_tx.shared::cta.b64 _, [%0], %1;" ::"r"(a), "r"(bytes) : "memory");
}
__device__ __forceinline__ void mbar_arrive_cluster(uint32_t a, uint32_t cta) {
  asm volatile("{\n.reg .b32 ra;\nmapa.shared::cluster.u32 ra, %0, %1;\nmbarrier.arrive.shared::cluster.b64 _, [ra];\n}\n" ::"r"(a), "r"(cta) : "memory");
}
__device__ __forceinline__ void mbar_arrive_both(uint32_t a) {
  mbar_arrive_cluster(a, 0); mbar_arrive_cluster(a, 1);
}
__device__ __forceinline__ void mbar_wait(uint32_t a, uint32_t parity, int code) {
  uint32_t ok = 0;
#pragma unroll 1
  for (uint32_t it = 0; it < SPIN_MAX; ++it) {
    asm volatile("{\n.reg .pred p;\nmbarrier.try_wait.parity.shared::cta.b64 p, [%1], %2;\nselp.u32 %0, 1, 0, p;\n}\n" : "=r"(ok) : "r"(a), "r"(parity) : "memory");
    if (ok) return;
  }
  FAIL(code);
}
__device__ __forceinline__ bool mbar_test(uint32_t a, uint32_t parity) {
  uint32_t ok;
  asm volatile("{\n.reg .pred p;\nmbarrier.test_wait.parity.shared::cta.b64 p, [%1], %2;\nselp.u32 %0, 1, 0, p;\n}\n" : "=r"(ok) : "r"(a), "r"(parity) : "memory");
  return __all_sync(0xffffffffu, ok != 0);
}
__device__ __forceinline__ void tma_load_2d(uint32_t dst, const CUtensorMap* map, int c0, int c1, uint32_t mbar) {
  asm volatile("cp.async.bulk.tensor.2d.shared::cluster.global.mbarrier::complete_tx::bytes [%0], [%1, {%3, %4}], [%2];" ::"r"(dst), "l"(map), "r"(mbar), "r"(c0), "r"(c1) : "memory");
}
__device__ __forceinline__ void tma_load_2d_mc(uint32_t dst, const CUtensorMap* map, int c0, int c1, uint32_t mbar, uint16_t mask) {
  asm volatile("cp.async.bulk.tensor.2d.shared::cluster.global.mbarrier::complete_tx::bytes.multicast::cluster [%0], [%1, {%3, %4}], [%2], %5;" ::"r"(dst), "l"(map), "r"(mbar), "r"(c0), "r"(c1), "h"(mask) : "memory");
}
__device__ __forceinline__ void tma_load_3d_mc(uint32_t dst, const CUtensorMap* map, int c0, int c1, int c2, uint32_t mbar, uint16_t mask) {
  asm volatile("cp.async.bulk.tensor.3d.shared::cluster.global.mbarrier::complete_tx::bytes.multicast::cluster [%0], [%1, {%3, %4, %5}], [%2], %6;" ::"r"(dst), "l"(map), "r"(mbar), "r"(c0), "r"(c1), "r"(c2), "h"(mask) : "memory");
}
__device__ __forceinline__ void tma_prefetch_3d(const CUtensorMap* map, int c0, int c1, int c2) {
  asm volatile("cp.async.bulk.prefetch.tensor.3d.L2.global.tile [%0, {%1, %2, %3}];" ::"l"(map), "r"(c0), "r"(c1), "r"(c2) : "memory");
}
__device__ __forceinline__ void wgmma_fence() { asm volatile("wgmma.fence.sync.aligned;" ::: "memory"); }
__device__ __forceinline__ void wgmma_commit() { asm volatile("wgmma.commit_group.sync.aligned;" ::: "memory"); }
template <int N> __device__ __forceinline__ void wgmma_wait() { asm volatile("wgmma.wait_group.sync.aligned %0;" ::"n"(N) : "memory"); }
__device__ __forceinline__ uint64_t make_desc(uint32_t saddr, uint32_t lbo, uint32_t sbo) {
  return (uint64_t)((saddr & 0x3FFFF) >> 4) | ((uint64_t)(lbo >> 4) << 16) | ((uint64_t)(sbo >> 4) << 32) | (1ull << 62);
}
__device__ __forceinline__ void fence_proxy_async() { asm volatile("fence.proxy.async.global;" ::: "memory"); }
__device__ __forceinline__ void named_bar(int id, int n) { asm volatile("bar.sync %0, %1;" ::"r"(id), "r"(n) : "memory"); }
__device__ __forceinline__ void cluster_sync() {
  asm volatile("barrier.cluster.arrive.release.aligned;\nbarrier.cluster.wait.acquire.aligned;" ::: "memory");
}
__device__ __forceinline__ unsigned ld_acquire(const unsigned* p) {
  unsigned v;
  asm volatile("ld.acquire.gpu.global.u32 %0, [%1];" : "=r"(v) : "l"(p) : "memory");
  return v;
}
__device__ __forceinline__ unsigned flag_wait(const unsigned* p, unsigned target, int code) {
#pragma unroll 1
  for (uint32_t it = 0; it < SPIN_MAX; ++it) {
    unsigned v = ld_acquire(p);
    if (v >= target) return v;
    __nanosleep(20);
  }
  FAIL(code);
  return 0;
}
__device__ __forceinline__ void flag_add(unsigned* p) {
  asm volatile("red.release.gpu.global.add.u32 [%0], 1;" ::"l"(p) : "memory");
}
__device__ __forceinline__ void agent_exit() {
  __threadfence();
  unsigned old = atomicAdd(&g_flags[272], 1u);
  if (old == NAGENTS - 1) {
    for (int i = 0; i < 273; ++i) g_flags[i] = 0;
    __threadfence();
  }
}
__device__ __forceinline__ float bf16r(float v) { return __bfloat162float(__float2bfloat16_rn(v)); }
__device__ __forceinline__ uint32_t pack_bf16(float lo, float hi) {
  uint32_t r;
  asm("cvt.rn.bf16x2.f32 %0, %1, %2;" : "=r"(r) : "f"(hi), "f"(lo));
  return r;
}
__device__ __forceinline__ void quad_transpose(uint32_t& v0, uint32_t& v1, uint32_t& v2, uint32_t& v3, int q) {
  bool b0 = q & 1;
  uint32_t s0 = b0 ? v0 : v1, s1 = b0 ? v2 : v3;
  s0 = __shfl_xor_sync(0xffffffffu, s0, 1);
  s1 = __shfl_xor_sync(0xffffffffu, s1, 1);
  if (b0) { v0 = s0; v2 = s1; } else { v1 = s0; v3 = s1; }
  bool b1 = q & 2;
  s0 = b1 ? v0 : v2; s1 = b1 ? v1 : v3;
  s0 = __shfl_xor_sync(0xffffffffu, s0, 2);
  s1 = __shfl_xor_sync(0xffffffffu, s1, 2);
  if (b1) { v0 = s0; v1 = s1; } else { v2 = s0; v3 = s1; }
}

struct Tile { int is_h; int col; int nb; };
__device__ __forceinline__ int num_tiles(int j) { return j ? 6 : 5; }
__device__ __forceinline__ Tile get_tile(int p, int j, int t) {
  Tile T;
  if (t == 0) {
    T.is_h = 0;
    if (j == 0) { T.col = 256 * p; T.nb = 4; }
    else { T.col = 1024 + 192 * p; T.nb = (p == 3) ? 2 : 3; }
  } else {
    T.is_h = 1; T.col = 128 * (9 * p + (j ? 4 : 0) + (t - 1)); T.nb = 4;
  }
  return T;
}

template <int NB> struct Acc { float a[NB * 32]; };
template <int NB> __device__ __forceinline__ void wgmma_nb(float (&d)[NB * 32], uint64_t da, uint64_t db, int sc);
template <> __device__ __forceinline__ void wgmma_nb<2>(float (&d)[64], uint64_t da, uint64_t db, int sc) { wgmma_n128(d, da, db, sc); }
template <> __device__ __forceinline__ void wgmma_nb<3>(float (&d)[96], uint64_t da, uint64_t db, int sc) { wgmma_n192(d, da, db, sc); }
template <> __device__ __forceinline__ void wgmma_nb<4>(float (&d)[128], uint64_t da, uint64_t db, int sc) { wgmma_n256(d, da, db, sc); }
template <int NB> __device__ __forceinline__ void wgmma_rs_nb(float (&d)[NB * 32], const uint32_t (&a)[4], uint64_t db);
template <> __device__ __forceinline__ void wgmma_rs_nb<2>(float (&d)[64], const uint32_t (&a)[4], uint64_t db) { wgmma_rs_n128(d, a, db); }
template <> __device__ __forceinline__ void wgmma_rs_nb<3>(float (&d)[96], const uint32_t (&a)[4], uint64_t db) { wgmma_rs_n192(d, a, db); }
template <> __device__ __forceinline__ void wgmma_rs_nb<4>(float (&d)[128], const uint32_t (&a)[4], uint64_t db) { wgmma_rs_n256(d, a, db); }

struct Ctx {
  uint32_t sbase;
  uint32_t full1, empty1, full2, empty2;
  uint32_t peer;
  int wg;
  int tid;
};

__device__ __forceinline__ void publish(unsigned* flag) {
  __threadfence();
  __syncwarp();
  if ((threadIdx.x & 31) == 0) flag_add(flag);
}
template <int NB>
__device__ __forceinline__ void g1_tile(const Ctx& c, float (&acc)[NB * 32], uint32_t& it  , const uint32_t (&areg)[8][4]) {
  const uint32_t abase = c.sbase + c.wg * 8192;
  wgmma_fence();
#pragma unroll 1
  for (int kb = 0; kb < 14; ++kb) {
    uint32_t s = it % NS1, ph = (it / NS1) & 1;
    bool rel = false;
    if (kb > 0 && !mbar_test(c.full1 + 8 * s, ph)) {
      wgmma_wait<0>();
      if (c.tid == 0) mbar_arrive_both(c.empty1 + 8 * ((it - 1) % NS1));
      rel = true;
    }
    mbar_wait(c.full1 + 8 * s, ph, 0);
    uint32_t a0 = abase + (kb >> 1) * 16384 + (kb & 1) * 64;
    uint32_t b0 = c.sbase + slot1_off(s);
    wgmma_nb<NB>(acc, make_desc(a0, 16, 1024), make_desc(b0, 4096, 1024), kb > 0);
    wgmma_nb<NB>(acc, make_desc(a0 + 32, 16, 1024), make_desc(b0 + 2048, 4096, 1024), 1);
    wgmma_commit();
    if (kb > 0 && !rel) {
      wgmma_wait<1>();
      if (c.tid == 0) mbar_arrive_both(c.empty1 + 8 * ((it - 1) % NS1));
    }
    ++it;
  }
#pragma unroll
  for (int kk = 0; kk < 4; ++kk) {
    uint32_t s = it % NS1, ph = (it / NS1) & 1;
    mbar_wait(c.full1 + 8 * s, ph, 0);
    uint32_t b0 = c.sbase + slot1_off(s);
    wgmma_rs_nb<NB>(acc, areg[2 * kk], make_desc(b0, 4096, 1024));
    wgmma_rs_nb<NB>(acc, areg[2 * kk + 1], make_desc(b0 + 2048, 4096, 1024));
    wgmma_commit();
    wgmma_wait<1>();
    if (c.tid == 0) mbar_arrive_both(c.empty1 + 8 * ((it - 1) % NS1));
    ++it;
  }
  wgmma_wait<0>();
  if (c.tid == 0) mbar_arrive_both(c.empty1 + 8 * ((it - 1) % NS1));
}

template <int NB>
__device__ __forceinline__ void epi_h(const Ctx& c, float (&acc)[NB * 32], int row0  , int hcol) {
  constexpr int G = NB * 4;
  const int lane = c.tid & 31, w = c.tid >> 5, q = lane & 3;
  const int r = row0 + c.wg * 64 + w * 16 + (lane >> 2);
  __nv_bfloat16* dst0 = g_act + (size_t)r * ACT_ + 576 + hcol + q * 8;
  __nv_bfloat16* dst1 = dst0 + 8 * ACT_;
  const __nv_bfloat162 zero2 = __floats2bfloat162_rn(0.f, 0.f);
#pragma unroll
  for (int a = 0; a < G / 4; ++a) {
    uint32_t v[4], u[4];
#pragma unroll
    for (int i = 0; i < 4; ++i) {
      int g = 4 * a + i;
      uint32_t g0 = pack_bf16(acc[4 * g], acc[4 * g + 1]), g1 = pack_bf16(acc[4 * g + 2], acc[4 * g + 3]);
      uint32_t u0 = pack_bf16(acc[4 * (g + G)], acc[4 * (g + G) + 1]), u1 = pack_bf16(acc[4 * (g + G) + 2], acc[4 * (g + G) + 3]);
      __nv_bfloat162 h0 = __hmul2(__hmax2(*(__nv_bfloat162*)&g0, zero2), *(__nv_bfloat162*)&u0);
      __nv_bfloat162 h1 = __hmul2(__hmax2(*(__nv_bfloat162*)&g1, zero2), *(__nv_bfloat162*)&u1);
      v[i] = *(uint32_t*)&h0; u[i] = *(uint32_t*)&h1;
    }
    quad_transpose(v[0], v[1], v[2], v[3], q);
    quad_transpose(u[0], u[1], u[2], u[3], q);
    *(uint4*)(dst0 + a * 32) = make_uint4(v[0], v[1], v[2], v[3]);
    *(uint4*)(dst1 + a * 32) = make_uint4(u[0], u[1], u[2], u[3]);
  }
}
template <int NB>
__device__ __forceinline__ void epi_qkv(const Ctx& c, float (&acc)[NB * 32], int row0, int col) {
  constexpr int G = NB * 8;
  const int lane = c.tid & 31, w = c.tid >> 5, q = lane & 3;
  const int r = row0 + c.wg * 64 + w * 16 + (lane >> 2);
  __nv_bfloat16* dst0 = g_qkv + (size_t)r * QKV_ + col + q * 8;
  __nv_bfloat16* dst1 = dst0 + 8 * QKV_;
#pragma unroll
  for (int a = 0; a < G / 4; ++a) {
    uint32_t v[4], u[4];
#pragma unroll
    for (int i = 0; i < 4; ++i) {
      int g = 4 * a + i;
      v[i] = pack_bf16(acc[4 * g], acc[4 * g + 1]); u[i] = pack_bf16(acc[4 * g + 2], acc[4 * g + 3]);
    }
    quad_transpose(v[0], v[1], v[2], v[3], q);
    quad_transpose(u[0], u[1], u[2], u[3], q);
    *(uint4*)(dst0 + a * 32) = make_uint4(v[0], v[1], v[2], v[3]);
    *(uint4*)(dst1 + a * 32) = make_uint4(u[0], u[1], u[2], u[3]);
  }
}
__device__ __forceinline__ void mbar_arrive_local(uint32_t a) { asm volatile("mbarrier.arrive.shared::cta.b64 _, [%0];" ::"r"(a) : "memory"); }

template <int NA>
__device__ __forceinline__ void acc_to_smem(float (&acc)[NA], uint32_t a0  , uint32_t pitch) {
#pragma unroll
  for (int g = 0; g < NA / 4; ++g) {
    asm volatile("st.shared.v2.f32 [%0], {%1, %2};" ::"r"(a0 + g * 32), "f"(acc[4 * g]), "f"(acc[4 * g + 1]) : "memory");
    asm volatile("st.shared.v2.f32 [%0], {%1, %2};" ::"r"(a0 + 8 * pitch + g * 32), "f"(acc[4 * g + 2]), "f"(acc[4 * g + 3]) : "memory");
  }
}
__device__ __forceinline__ float4 lds128(uint32_t a) {
  float4 v;
  asm volatile("ld.shared.v4.f32 {%0, %1, %2, %3}, [%4];" : "=f"(v.x), "=f"(v.y), "=f"(v.z), "=f"(v.w) : "r"(a) : "memory");
  return v;
}

__device__ __forceinline__ void mma16816(float (&c)[4], uint32_t a0, uint32_t a1, uint32_t a2, uint32_t a3, uint32_t b0, uint32_t b1) {
  asm volatile("mma.sync.aligned.m16n8k16.row.col.f32.bf16.bf16.f32 {%0,%1,%2,%3}, {%4,%5,%6,%7}, {%8,%9}, {%0,%1,%2,%3};"
               : "+f"(c[0]), "+f"(c[1]), "+f"(c[2]), "+f"(c[3]) : "r"(a0), "r"(a1), "r"(a2), "r"(a3), "r"(b0), "r"(b1));
}
__device__ __forceinline__ uint32_t movm(uint32_t a) {
  uint32_t d;
  asm volatile("movmatrix.sync.aligned.m8n8.trans.b16 %0, %1;" : "=r"(d) : "r"(a));
  return d;
}
struct HeadRegs { uint32_t q[2][3], k[4][3], v[4][3]; };
__device__ __forceinline__ void load_head(HeadRegs& R, int h, int qrow, int g, int t) {
  const int o = h & 1;
  const int wp = 9 * h + o + 2 * t, wt = 9 * h + (o ? 0 : 8);
#pragma unroll
  for (int r = 0; r < 2; ++r) {
    const uint32_t* p = (const uint32_t*)(g_qkv + (size_t)(qrow + g + 8 * r) * QKV_);
    uint2 a = *(const uint2*)(p + wp);
    R.q[r][0] = a.x; R.q[r][1] = a.y; R.q[r][2] = t == 0 ? p[wt] : 0u;
  }
#pragma unroll
  for (int nt = 0; nt < 4; ++nt) {
    const int jj = 8 * nt + g, kr = qrow - 14 + jj;
    const bool ok = (kr >= 0) && (jj < 30);
    const uint32_t* p = (const uint32_t*)(g_qkv + (size_t)(ok ? kr : qrow) * QKV_);
    uint2 a = make_uint2(0u, 0u);
    if (ok) a = *(const uint2*)(p + 288 + wp);
    R.k[nt][0] = a.x; R.k[nt][1] = a.y; R.k[nt][2] = (ok && t == 0) ? p[288 + wt] : 0u;
    R.v[nt][0] = ok ? p[576 + 9 * h + t] : 0u; R.v[nt][1] = ok ? p[576 + 9 * h + 4 + t] : 0u;
    R.v[nt][2] = (ok && t == 0) ? p[576 + 9 * h + 8] : 0u;
  }
}
__device__ __noinline__ void attention(int row0, int role, int m, int aw, int lane) {
  if (lane < 8) flag_wait(&g_flags[m * 8 + lane], 1, 5);
  else if (lane < 16 && role == 0 && m > 0) flag_wait(&g_flags[(m - 1) * 8 + lane - 8], 1, 5);
  __syncwarp();
  if (aw == 0 && lane == 0) TS2(24);
  const float scale = 0.23570226039551584f;
  const int g = lane >> 2, t = lane & 3;
  const int qrow = row0 + role * 16;
  HeadRegs N;
  load_head(N, aw, qrow, g, t);
#pragma unroll 1
  for (int h = aw; h < 32; h += 8) {
    HeadRegs R = N;
    if (h + 8 < 32) load_head(N, h + 8, qrow, g, t);
    float sc[4][4];
#pragma unroll
    for (int nt = 0; nt < 4; ++nt) {
      sc[nt][0] = sc[nt][1] = sc[nt][2] = sc[nt][3] = 0.f;
      mma16816(sc[nt], R.q[0][0], R.q[1][0], R.q[0][1], R.q[1][1], R.k[nt][0], R.k[nt][1]);
      mma16816(sc[nt], R.q[0][2], R.q[1][2], 0u, 0u, R.k[nt][2], 0u);
    }
    const int par = g & 1;
    float l0[4], l1[4];
    float mx0 = -3.0e38f, mx1 = -3.0e38f;
#pragma unroll
    for (int nt = 0; nt < 4; ++nt) {
      const int jj = 8 * nt + 2 * t + par;
      const int d0 = g + 14 - jj, d1 = d0 + 8;
      const bool inr = qrow - 14 + jj >= 0;
      const bool ok0 = inr && d0 >= 0 && d0 <= 14, ok1 = inr && d1 >= 0 && d1 <= 14;
      uint32_t pk = pack_bf16(par ? sc[nt][1] : sc[nt][0], par ? sc[nt][3] : sc[nt][2]);
      pk = pack_bf16(__uint_as_float(pk << 16) * scale, __uint_as_float(pk & 0xffff0000u) * scale);
      l0[nt] = ok0 ? __uint_as_float(pk << 16) : -3.0e38f;
      l1[nt] = ok1 ? __uint_as_float(pk & 0xffff0000u) : -3.0e38f;
      mx0 = fmaxf(mx0, l0[nt]); mx1 = fmaxf(mx1, l1[nt]);
    }
    mx0 = fmaxf(mx0, __shfl_xor_sync(0xffffffffu, mx0, 1)); mx0 = fmaxf(mx0, __shfl_xor_sync(0xffffffffu, mx0, 2));
    mx1 = fmaxf(mx1, __shfl_xor_sync(0xffffffffu, mx1, 1)); mx1 = fmaxf(mx1, __shfl_xor_sync(0xffffffffu, mx1, 2));
    float s0 = 0.f, s1 = 0.f;
#pragma unroll
    for (int nt = 0; nt < 4; ++nt) {
      l0[nt] = __expf(l0[nt] - mx0); l1[nt] = __expf(l1[nt] - mx1);
      s0 += l0[nt]; s1 += l1[nt];
    }
    s0 += __shfl_xor_sync(0xffffffffu, s0, 1); s0 += __shfl_xor_sync(0xffffffffu, s0, 2);
    s1 += __shfl_xor_sync(0xffffffffu, s1, 1); s1 += __shfl_xor_sync(0xffffffffu, s1, 2);
    const float i0 = __frcp_rn(s0), i1 = __frcp_rn(s1);
    uint32_t pa[2][4];
#pragma unroll
    for (int nt = 0; nt < 4; ++nt) {
      const float p0 = l0[nt] * i0, p1 = l1[nt] * i1;
      pa[nt >> 1][(nt & 1) * 2] = par ? pack_bf16(0.f, p0) : pack_bf16(p0, 0.f);
      pa[nt >> 1][(nt & 1) * 2 + 1] = par ? pack_bf16(0.f, p1) : pack_bf16(p1, 0.f);
    }
    uint32_t* o0p = (uint32_t*)(g_act + (size_t)(qrow + g) * ACT_) + 9 * h;
    uint32_t* o1p = (uint32_t*)(g_act + (size_t)(qrow + g + 8) * ACT_) + 9 * h;
#pragma unroll
    for (int cg = 0; cg < 3; ++cg) {
      float oc[4] = {0.f, 0.f, 0.f, 0.f};
      mma16816(oc, pa[0][0], pa[0][1], pa[0][2], pa[0][3], movm(R.v[0][cg]), movm(R.v[1][cg]));
      mma16816(oc, pa[1][0], pa[1][1], pa[1][2], pa[1][3], movm(R.v[2][cg]), movm(R.v[3][cg]));
      if (cg < 2 || t == 0) {
        o0p[4 * cg + t] = pack_bf16(oc[0], oc[1]);
        o1p[4 * cg + t] = pack_bf16(oc[2], oc[3]);
      }
    }
  }
  if (aw == 0 && lane == 0) TS2(26);
}

__global__ void __cluster_dims__(2, 1, 1) __launch_bounds__(384, 1)
fused_kernel(const __grid_constant__ CUtensorMap m_qkv1, const __grid_constant__ CUtensorMap m_qkv2,
             const __grid_constant__ CUtensorMap m_gate2, const __grid_constant__ CUtensorMap m_up2,
             const __grid_constant__ CUtensorMap m_wo5, const __grid_constant__ CUtensorMap m_wo4,
             const __grid_constant__ CUtensorMap m_down5, const __grid_constant__ CUtensorMap m_down4,
             const __grid_constant__ CUtensorMap m_act,
             const __nv_bfloat16* __restrict__ x, __nv_bfloat16* __restrict__ out) {
  extern __shared__ uint8_t smem_raw[];
  const uint32_t sbase = (smem_u32(smem_raw) + 1023) & ~1023u;
  const uint32_t bars = sbase + DATA_BYTES;
  const uint32_t full1 = bars, empty1 = bars + 64, full2 = bars + 128, empty2 = bars + 192, pub = bars + 256;
  const int rank = blockIdx.x & 1, cl = blockIdx.x >> 1;
  const int role = cl & 7, m = (cl >> 3) * 2 + rank, p = role >> 1, j = role & 1;
  const int row0 = m * 128;
  const int warp = __shfl_sync(0xffffffffu, (int)(threadIdx.x >> 5), 0), lane = threadIdx.x & 31;
  const int nkb2 = (p == 3) ? 21 : 20;
  const int nblk2 = j ? 4 : 5;
  const int ncol0 = j ? 320 : 0;

  uint4 nx[9];
  if (warp >= 4) {
    const int cw = warp - 4;
    const uint4* src = (const uint4*)(x + (size_t)(row0 + cw * 16 + (lane >> 3)) * D_) + (lane & 7);
#pragma unroll
    for (int t = 0; t < 9; ++t) nx[t] = __ldg(src + 8 * t);
  }
  if (threadIdx.x == 0) {
    for (int s = 0; s < NS1; ++s) { mbar_init(full1 + 8 * s, 1); mbar_init(empty1 + 8 * s, MC ? 4 : 2); }
    for (int s = 0; s < NS2; ++s) { mbar_init(full2 + 8 * s, 1); mbar_init(empty2 + 8 * s, MC ? 4 : 2); }
    for (int s = 0; s < 7; ++s) mbar_init(pub + 8 * s, 256);
    asm volatile("fence.mbarrier_init.release.cluster;" ::: "memory");
  }
  __syncthreads();
  cluster_sync();

  if (warp < 4) {
    asm volatile("setmaxnreg.dec.sync.aligned.u32 40;");
    if (warp == 0) {
      if (lane == 0) {
        uint32_t it = 0;
        const int nt = num_tiles(j);
        volatile uint32_t* known = (volatile uint32_t*)(smem_raw + (bars + 320 - smem_u32(smem_raw)));
        volatile uint32_t* sched = known + 12;
        for (int t = 0; t < nt; ++t) {
          Tile T = get_tile(p, j, t);
          const CUtensorMap* mp; int cb, nmine;
          if (T.is_h) { mp = rank ? &m_up2 : &m_gate2; cb = T.col >> 6; nmine = 2; }
          else if (T.nb == 4) { mp = &m_qkv2; cb = (T.col >> 6) + 2 * rank; nmine = 2; }
          else if (T.nb == 3) { mp = rank ? &m_qkv1 : &m_qkv2; cb = (T.col >> 6) + 2 * rank; nmine = rank ? 1 : 2; }
          else { mp = &m_qkv1; cb = (T.col >> 6) + rank; nmine = 1; }
          const uint32_t doff = (T.nb == 2 ? rank : 2 * rank) * 4096;
          for (int kb = 0; kb < 18; ++kb, ++it) {
            uint32_t s = it % NS1, ph = (it / NS1) & 1;
            if (it == 5) {
              for (int r = 0; r < 9; ++r) known[r] = 0;
              const int hlo = p == 0 ? 0 : 20 * p - 9, hhi = 20 * p + 11 + (p == 3 ? 1 : 0);
              int n = 0;
              for (int tt = 1; tt <= 5; ++tt)
                for (int hb = hlo; hb < hhi; ++hb) {
                  int TT = hb >> 1, pp = TT / 9, idx = TT - 9 * pp;
                  int ot = 1 + (idx >= 4 ? idx - 4 : idx);
                  if (ot == tt) sched[n++] = (uint32_t)hb | ((uint32_t)(2 * pp + (idx >= 4)) << 8) | ((uint32_t)(ot + 1) << 16);
                }
            }
            mbar_wait(empty1 + 8 * s, s >= 5 ? ph : ph ^ 1, 1);
            mbar_expect_tx(full1 + 8 * s, T.nb * 4096);
            tma_load_3d_mc(sbase + slot1_off(s) + doff, mp, 0, kb * 32, cb, full1 + 8 * s, 3);
            (void)nmine;
          }
        }
        const CUtensorMap* mwo = j ? &m_wo4 : &m_wo5;
        const CUtensorMap* mdn = j ? &m_down4 : &m_down5;
        for (int i = 0; i < nkb2; ++i) {
          uint32_t s = i % NS2, ph = (i / NS2) & 1;
          int acol, kn, wrow; const CUtensorMap* mp; const unsigned* fl; unsigned tgt;
          if (p == 0 && i >= 11) {
            acol = (i - 11) * 64; mp = mwo; wrow = acol; fl = &g_flags[128 + m]; tgt = 8; kn = 8;
          } else {
            uint32_t e = sched[i];
            wrow = (e & 255) * 64; kn = (e >> 8) & 255; tgt = e >> 16;
            acol = 576 + wrow; mp = mdn; fl = &g_flags[m * 8 + kn];
          }
          mbar_wait(empty2 + 8 * s, ph, 2);
          mbar_expect_tx(full2 + 8 * s, 16384 + nblk2 * 8192);
          uint32_t dst = sbase + s * ST2_BYTES;
          tma_load_3d_mc(dst + 16384 + rank * nblk2 * 4096, mp, 0, wrow + 32 * rank, ncol0 >> 6, full2 + 8 * s, 3);
          if (known[kn] < tgt) { known[kn] = flag_wait(fl, tgt, 4); fence_proxy_async(); }
          tma_load_2d(dst, &m_act, acol, row0, full2 + 8 * s);
          TS2(32 + i);
        }
        agent_exit();
      }
    } else if (warp == 1) {
      const int nt = num_tiles(j);
      for (int t = 0; t < nt; ++t) {
        mbar_wait(pub + 8 * t, 0, 7);
        if (lane == 0) { if (t == 0) TS2(27); __threadfence(); flag_add(&g_flags[m * 8 + role]); if (t == 0) TS2(28); }
        __syncwarp();
        if (t == 1) {
          mbar_wait(pub + 8 * 6, 0, 7);
          if (lane == 0) { __threadfence(); flag_add(&g_flags[128 + m]); }
          __syncwarp();
        }
      }
      if (lane == 0) agent_exit();
    } else if (warp == 2) {
      if (lane == 0) {
        const int mp8 = cl >> 3, nt = num_tiles(j);
        for (int t = 1; t <= nt; ++t) {
          if (t >= 2) mbar_wait(pub + 8 * (t - 2), 0, 7);
          if (t < nt) {
            Tile T = get_tile(p, j, t);
            for (int kb = mp8; kb < 18; kb += 8) tma_prefetch_3d(rank ? &m_up2 : &m_gate2, 0, kb * 32, T.col >> 6);
          } else {
            const int hlo = p == 0 ? 0 : 20 * p - 9, hhi = 20 * p + 11 + (p == 3 ? 1 : 0);
            for (int hb = hlo + mp8; hb < hhi; hb += 8) tma_prefetch_3d(j ? &m_down4 : &m_down5, 0, hb * 64 + 32 * rank, ncol0 >> 6);
            if (p == 0) for (int ob = mp8; ob < 9; ob += 8) tma_prefetch_3d(j ? &m_wo4 : &m_wo5, 0, ob * 64 + 32 * rank, ncol0 >> 6);
          }
        }
      }
    }
  } else {
    asm volatile("setmaxnreg.inc.sync.aligned.u32 232;");
    Ctx c;
    c.sbase = sbase; c.full1 = full1; c.empty1 = empty1; c.full2 = full2; c.empty2 = empty2; c.peer = rank ^ 1;
    c.wg = (warp - 4) >> 2; c.tid = threadIdx.x - 128 - c.wg * 128;
    const int w = c.tid >> 5;
    if (c.wg == 0 && c.tid == 0) TS(0);
    uint32_t areg[8][4];
    {
      const int sub = lane >> 3, li = lane & 7;
#pragma unroll 1
      for (int itr = 0; itr < 4; ++itr) {
        const int r = c.wg * 64 + w * 16 + itr * 4 + sub;
        uint4 xv[9];
#pragma unroll
        for (int t = 0; t < 9; ++t) xv[t] = nx[t];
        if (itr < 3) {
          const uint4* src = (const uint4*)(x + (size_t)(row0 + r + 4) * D_) + li;
#pragma unroll
          for (int t = 0; t < 9; ++t) nx[t] = __ldg(src + 8 * t);
        }
        float s0 = 0.f, s1 = 0.f;
#pragma unroll
        for (int t = 0; t < 9; ++t) {
          const uint32_t* u = (const uint32_t*)&xv[t];
#pragma unroll
          for (int e = 0; e < 4; ++e) { s0 += __uint_as_float(u[e] << 16); s1 += __uint_as_float(u[e] & 0xffff0000u); }
        }
        float sum = s0 + s1;
        sum += __shfl_xor_sync(0xffffffffu, sum, 1); sum += __shfl_xor_sync(0xffffffffu, sum, 2); sum += __shfl_xor_sync(0xffffffffu, sum, 4);
        const float mean = sum * (1.f / 576.f);
        float q0 = 0.f, q1 = 0.f;
#pragma unroll
        for (int t = 0; t < 9; ++t) {
          const uint32_t* u = (const uint32_t*)&xv[t];
#pragma unroll
          for (int e = 0; e < 4; ++e) {
            float a = __uint_as_float(u[e] << 16) - mean, b = __uint_as_float(u[e] & 0xffff0000u) - mean;
            q0 = fmaf(a, a, q0); q1 = fmaf(b, b, q1);
          }
        }
        float sq = q0 + q1;
        sq += __shfl_xor_sync(0xffffffffu, sq, 1); sq += __shfl_xor_sync(0xffffffffu, sq, 2); sq += __shfl_xor_sync(0xffffffffu, sq, 4);
        const float vb = bf16r(sq * (1.f / 576.f));
        const float rinv = 1.f / bf16r(sqrtf(bf16r(vb + 1e-5f)));
        const __nv_bfloat162 mb2 = __float2bfloat162_rn(mean);
        const uint32_t dsta = sbase + r * 128 + ((li ^ (r & 7)) << 4);
#pragma unroll
        for (int t = 0; t < 9; ++t) {
          const uint32_t* u = (const uint32_t*)&xv[t];
          uint32_t o[4];
#pragma unroll
          for (int e = 0; e < 4; ++e) {
            __nv_bfloat162 d2 = __hsub2(*(const __nv_bfloat162*)&u[e], mb2);
            uint32_t du = *(uint32_t*)&d2;
            o[e] = pack_bf16(__uint_as_float(du << 16) * rinv, __uint_as_float(du & 0xffff0000u) * rinv);
          }
          asm volatile("st.shared.v4.b32 [%0], {%1, %2, %3, %4};" ::"r"(dsta + t * 16384), "r"(o[0]), "r"(o[1]), "r"(o[2]), "r"(o[3]) : "memory");
        }
      }
      asm volatile("fence.proxy.async.shared::cta;" ::: "memory");
      __syncwarp();
      {
        const int r = c.wg * 64 + w * 16 + (lane & 7) + ((lane >> 3) & 1) * 8;
        const int hi = lane >> 4;
#pragma unroll
        for (int ks = 0; ks < 8; ++ks) {
          const uint32_t ad = sbase + (7 + (ks >> 2)) * 16384 + r * 128 + ((((ks & 3) * 2 + hi) ^ (r & 7)) << 4);
          asm volatile("ldmatrix.sync.aligned.m8n8.x4.shared.b16 {%0, %1, %2, %3}, [%4];"
                       : "=r"(areg[ks][0]), "=r"(areg[ks][1]), "=r"(areg[ks][2]), "=r"(areg[ks][3]) : "r"(ad) : "memory");
        }
      }
      named_bar(1 + c.wg, 128);
      if (c.tid == 0) { mbar_arrive_both(empty1 + 8 * 5); mbar_arrive_both(empty1 + 8 * 6); }
      if (c.wg == 1) {
        const long long t0 = clock64();
        while (clock64() - t0 < SKEW) {}
      }
    }
    if (c.wg == 0 && c.tid == 0) TS(1);
    unsigned* myflag = &g_flags[m * 8 + role];
    {
      uint32_t it = 0;
      const int nt = num_tiles(j);
#pragma unroll 1
      for (int t = 0; t < nt; ++t) {
        Tile T = get_tile(p, j, t);
        if (T.nb == 4) {
          float acc[128] = {};
          g1_tile<4>(c, acc, it, areg);
          if (T.is_h) epi_h<4>(c, acc, row0, T.col); else epi_qkv<4>(c, acc, row0, T.col);
        } else if (T.nb == 3) {
          float acc[96] = {};
          g1_tile<3>(c, acc, it, areg);
          epi_qkv<3>(c, acc, row0, T.col);
        } else {
          float acc[64] = {};
          g1_tile<2>(c, acc, it, areg);
          epi_qkv<2>(c, acc, row0, T.col);
        }
        if (t == nt - 1 && c.tid == 0) {
          for (int s = 0; s < NS2; ++s) { mbar_arrive_both(empty2 + 8 * s); }
        }
        mbar_arrive_local(pub + 8 * t);
        if (t == 1) {
          if (c.wg == 0 && c.tid == 0) TS(11);
          attention(row0, role, m, c.wg * 4 + w, lane);
          mbar_arrive_local(pub + 8 * 6);
          if (c.wg == 0 && c.tid == 0) TS(12);
        }
        if (c.wg == 0 && c.tid == 0) TS(2 + t);
      }
    }
    const int nch = j ? 32 : 40;
    const uint32_t pitch = nch * 32 + 32;
    const uint32_t sacc = sbase + (c.wg * 64 + w * 16 + (lane >> 2)) * pitch + (lane & 3) * 8;
    if (j == 0) {
      float acc1[96] = {}, acc2[64] = {};
      wgmma_fence();
#pragma unroll 1
      for (int i = 0; i < nkb2; ++i) {
        uint32_t s = i % NS2, ph = (i / NS2) & 1;
        mbar_wait(full2 + 8 * s, ph, 3);
        if (c.wg == 0 && c.tid == 0) TS2(i);
        uint32_t a0 = sbase + s * ST2_BYTES + c.wg * 8192, b0 = sbase + s * ST2_BYTES + 16384;
#pragma unroll
        for (int k = 0; k < 4; ++k) {
          uint64_t da = make_desc(a0 + k * 32, 16, 1024);
          const uint32_t bk = b0 + (k >> 1) * (5 * 4096) + (k & 1) * 2048;
          wgmma_n192(acc1, da, make_desc(bk, 4096, 1024), (i | k) != 0);
          wgmma_n128(acc2, da, make_desc(bk + 3 * 4096, 4096, 1024), (i | k) != 0);
        }
        wgmma_commit();
        if (i > 0) {
          wgmma_wait<1>();
          if (c.tid == 0 && i - 1 + NS2 < nkb2) { uint32_t sp = (i - 1) % NS2; mbar_arrive_both(empty2 + 8 * sp); }
        }
      }
      wgmma_wait<0>();
      if (c.wg == 0 && c.tid == 0) TS(8);
      named_bar(3, 256);
      acc_to_smem<96>(acc1, sacc, pitch);
      acc_to_smem<64>(acc2, sacc + 768, pitch);
    } else {
      float acc[128] = {};
      wgmma_fence();
#pragma unroll 1
      for (int i = 0; i < nkb2; ++i) {
        uint32_t s = i % NS2, ph = (i / NS2) & 1;
        mbar_wait(full2 + 8 * s, ph, 3);
        if (c.wg == 0 && c.tid == 0) TS2(i);
        uint32_t a0 = sbase + s * ST2_BYTES + c.wg * 8192, b0 = sbase + s * ST2_BYTES + 16384;
#pragma unroll
        for (int k = 0; k < 4; ++k)
          wgmma_n256(acc, make_desc(a0 + k * 32, 16, 1024), make_desc(b0 + (k >> 1) * (4 * 4096) + (k & 1) * 2048, 4096, 1024), (i | k) != 0);
        wgmma_commit();
        if (i > 0) {
          wgmma_wait<1>();
          if (c.tid == 0 && i - 1 + NS2 < nkb2) { uint32_t sp = (i - 1) % NS2; mbar_arrive_both(empty2 + 8 * sp); }
        }
      }
      wgmma_wait<0>();
      if (c.wg == 0 && c.tid == 0) TS(8);
      named_bar(3, 256);
      acc_to_smem<128>(acc, sacc, pitch);
    }
    named_bar(3, 256);
    {
      const int t256 = c.wg * 128 + c.tid;
      uint4* xs = g_xch + (size_t)((m * 2 + j) * 4) * 128 * 40;
      unsigned* pf = &g_flags[144 + (m * 2 + j) * 4];
#pragma unroll 1
      for (int e = t256; e < 96 * nch; e += 256) {
        int r = e / nch, cI = e - r * nch;
        r += (r >= 32 * p) ? 32 : 0;
        float4 u0 = lds128(sbase + r * pitch + cI * 32), u1 = lds128(sbase + r * pitch + cI * 32 + 16);
        xs[((size_t)p * 128 + r) * 40 + cI] = make_uint4(pack_bf16(u0.x, u0.y), pack_bf16(u0.z, u0.w), pack_bf16(u1.x, u1.y), pack_bf16(u1.z, u1.w));
      }
      __threadfence();
      __syncwarp();
      if (lane < 4 && lane != p) flag_add(pf + lane);
      if (lane == 0) flag_wait(pf + p, 24, 6);
      __syncwarp();
      if (c.wg == 0 && c.tid == 0) TS(9);
      const int nit = nch >> 3;
#pragma unroll
      for (int i = 0; i < 5; ++i) {
        if (i < nit) {
          const int e = t256 + i * 256;
          const int rl = e / nch, cI = e - rl * nch, r = 32 * p + rl;
          uint4 v[3];
#pragma unroll
          for (int k = 0; k < 3; ++k) v[k] = __ldcg(xs + ((size_t)(k + (k >= p)) * 128 + r) * 40 + cI);
          const size_t off = (size_t)(row0 + r) * D_ + ncol0 + cI * 8;
          const uint4 xv = __ldg((const uint4*)(x + off));
          float4 u0 = lds128(sbase + r * pitch + cI * 32), u1 = lds128(sbase + r * pitch + cI * 32 + 16);
          float f[8] = {u0.x, u0.y, u0.z, u0.w, u1.x, u1.y, u1.z, u1.w};
          uint32_t o[4];
#pragma unroll
          for (int e2 = 0; e2 < 4; ++e2) {
            const uint32_t w0 = ((const uint32_t*)&v[0])[e2], w1 = ((const uint32_t*)&v[1])[e2], w2 = ((const uint32_t*)&v[2])[e2], w3 = ((const uint32_t*)&xv)[e2];
            float lo = f[2 * e2] + ((__uint_as_float(w0 << 16) + __uint_as_float(w1 << 16)) + (__uint_as_float(w2 << 16) + __uint_as_float(w3 << 16)));
            float hi = f[2 * e2 + 1] + ((__uint_as_float(w0 & 0xffff0000u) + __uint_as_float(w1 & 0xffff0000u)) + (__uint_as_float(w2 & 0xffff0000u) + __uint_as_float(w3 & 0xffff0000u)));
            o[e2] = pack_bf16(lo, hi);
          }
          *(uint4*)(out + off) = make_uint4(o[0], o[1], o[2], o[3]);
        }
      }
      if (c.wg == 0 && c.tid == 0) TS(10);
    }
    named_bar(1 + c.wg, 128);
    if (c.tid == 0) agent_exit();
  }
}

typedef CUresult (*EncodeFn)(CUtensorMap*, CUtensorMapDataType, cuuint32_t, void*, const cuuint64_t*, const cuuint64_t*,
                             const cuuint32_t*, const cuuint32_t*, CUtensorMapInterleave, CUtensorMapSwizzle,
                             CUtensorMapL2promotion, CUtensorMapFloatOOBfill);

static void make_map2(EncodeFn enc, CUtensorMap* mp, const void* ptr, int rows, int cols, int box_rows) {
  cuuint64_t dims[2] = {(cuuint64_t)cols, (cuuint64_t)rows};
  cuuint64_t strides[1] = {(cuuint64_t)cols * 2};
  cuuint32_t box[2] = {64, (cuuint32_t)box_rows};
  cuuint32_t es[2] = {1, 1};
  enc(mp, CU_TENSOR_MAP_DATA_TYPE_BFLOAT16, 2, (void*)ptr, dims, strides, box, es, CU_TENSOR_MAP_INTERLEAVE_NONE,
      CU_TENSOR_MAP_SWIZZLE_128B, CU_TENSOR_MAP_L2_PROMOTION_L2_256B, CU_TENSOR_MAP_FLOAT_OOB_FILL_NONE);
}
static void make_map3(EncodeFn enc, CUtensorMap* mp, const void* ptr, int rows, int cols, int nblk) {
  cuuint64_t dims[3] = {64, (cuuint64_t)rows, (cuuint64_t)(cols / 64)};
  cuuint64_t strides[2] = {(cuuint64_t)cols * 2, 128};
  cuuint32_t box[3] = {64, 32, (cuuint32_t)nblk};
  cuuint32_t es[3] = {1, 1, 1};
  enc(mp, CU_TENSOR_MAP_DATA_TYPE_BFLOAT16, 3, (void*)ptr, dims, strides, box, es, CU_TENSOR_MAP_INTERLEAVE_NONE,
      CU_TENSOR_MAP_SWIZZLE_128B, CU_TENSOR_MAP_L2_PROMOTION_L2_256B, CU_TENSOR_MAP_FLOAT_OOB_FILL_NONE);
}

extern "C" void kernel_launch(void* const* d_in, const int* in_sizes, int n_in, void* d_out, int out_size) {
  static EncodeFn enc = nullptr;
  static void* act_ptr = nullptr;
  if (!enc) {
    void* fn = nullptr;
    cudaDriverEntryPointQueryResult qr;
    cudaGetDriverEntryPoint("cuTensorMapEncodeTiled", &fn, cudaEnableDefault, &qr);
    enc = (EncodeFn)fn;
    cudaGetSymbolAddress(&act_ptr, g_act);
    cudaFuncSetAttribute(fused_kernel, cudaFuncAttributeMaxDynamicSharedMemorySize, SMEM_BYTES);
  }
  const __nv_bfloat16* x = (const __nv_bfloat16*)d_in[0];
  CUtensorMap m_qkv1, m_qkv2, m_gate2, m_up2, m_wo5, m_wo4, m_down5, m_down4, m_act;
  make_map3(enc, &m_qkv1, d_in[1], D_, QKV_, 1);
  make_map3(enc, &m_qkv2, d_in[1], D_, QKV_, 2);
  make_map3(enc, &m_gate2, d_in[4], D_, F_, 2);
  make_map3(enc, &m_up2, d_in[5], D_, F_, 2);
  make_map3(enc, &m_wo5, d_in[2], D_, D_, 5);
  make_map3(enc, &m_wo4, d_in[2], D_, D_, 4);
  make_map3(enc, &m_down5, d_in[6], F_, D_, 5);
  make_map3(enc, &m_down4, d_in[6], F_, D_, 4);
  make_map2(enc, &m_act, act_ptr, S_, ACT_, 128);
  fused_kernel<<<128, 384, SMEM_BYTES>>>(m_qkv1, m_qkv2, m_gate2, m_up2, m_wo5, m_wo4, m_down5, m_down4, m_act, x, (__nv_bfloat16*)d_out);
}
```

```cpp
#include <cuda_runtime.h>
#include <cuda_bf16.h>
#include <cuda.h>
#include <stdint.h>

constexpr int S_ = 2048, D_ = 576, F_ = 4608, QKV_ = 1728, ACT_ = 5184;
constexpr int NS1 = 7;
constexpr int NS2 = 4;
constexpr int XN_BYTES = 9 * 16384;
constexpr int RING1_OFF = 7 * 16384;
__device__ __forceinline__ uint32_t slot1_off(uint32_t s) { return RING1_OFF + (s >= 5 ? s - 5 : s + 2) * 16384; }
constexpr int ST1_BYTES = 16384;
constexpr int ST2_BYTES = 57344;
constexpr int DATA_BYTES = 229376;
constexpr int SMEM_BYTES = DATA_BYTES + 1024 + 512;
constexpr int NAGENTS = 128 * 4;
#define SKEW 0
#define MC 1

__device__ __align__(1024) __nv_bfloat16 g_qkv[S_ * QKV_];
__device__ __align__(1024) __nv_bfloat16 g_act[S_ * ACT_];
__device__ __align__(1024) uint4 g_xch[16 * 2 * 4 * 128 * 40];
__device__ unsigned int g_flags[288];
#define TS(i)
#define TS2(i)
#define FAIL(code) __trap()
#define SPIN_MAX (1u << 24)

__device__ __forceinline__ void wgmma_n128(float (&d)[64], uint64_t da, uint64_t db, int scale_d) {
  asm volatile("{\n.reg .pred p;\nsetp.ne.b32 p, %66, 0;\n"
    "wgmma.mma_async.sync.aligned.m64n128k16.f32.bf16.bf16 {%0, %1, %2, %3, %4, %5, %6, %7, %8, %9, %10, %11, %12, %13, %14, %15, %16, %17, %18, %19, %20, %21, %22, %23, %24, %25, %26, %27, %28, %29, %30, %31, %32, %33, %34, %35, %36, %37, %38, %39, %40, %41, %42, %43, %44, %45, %46, %47, %48, %49, %50, %51, %52, %53, %54, %55, %56, %57, %58, %59, %60, %61, %62, %63}, %64, %65, p, 1, 1, 0, 1;\n}\n"
    : "+f"(d[0]), "+f"(d[1]), "+f"(d[2]), "+f"(d[3]), "+f"(d[4]), "+f"(d[5]), "+f"(d[6]), "+f"(d[7]), "+f"(d[8]), "+f"(d[9]), "+f"(d[10]), "+f"(d[11]), "+f"(d[12]), "+f"(d[13]), "+f"(d[14]), "+f"(d[15]), "+f"(d[16]), "+f"(d[17]), "+f"(d[18]), "+f"(d[19]), "+f"(d[20]), "+f"(d[21]), "+f"(d[22]), "+f"(d[23]), "+f"(d[24]), "+f"(d[25]), "+f"(d[26]), "+f"(d[27]), "+f"(d[28]), "+f"(d[29]), "+f"(d[30]), "+f"(d[31]), "+f"(d[32]), "+f"(d[33]), "+f"(d[34]), "+f"(d[35]), "+f"(d[36]), "+f"(d[37]), "+f"(d[38]), "+f"(d[39]), "+f"(d[40]), "+f"(d[41]), "+f"(d[42]), "+f"(d[43]), "+f"(d[44]), "+f"(d[45]), "+f"(d[46]), "+f"(d[47]), "+f"(d[48]), "+f"(d[49]), "+f"(d[50]), "+f"(d[51]), "+f"(d[52]), "+f"(d[53]), "+f"(d[54]), "+f"(d[55]), "+f"(d[56]), "+f"(d[57]), "+f"(d[58]), "+f"(d[59]), "+f"(d[60]), "+f"(d[61]), "+f"(d[62]), "+f"(d[63])
    : "l"(da), "l"(db), "r"(scale_d));
}

__device__ __forceinline__ void wgmma_n192(float (&d)[96], uint64_t da, uint64_t db, int scale_d) {
  asm volatile("{\n.reg .pred p;\nsetp.ne.b32 p, %98, 0;\n"
    "wgmma.mma_async.sync.aligned.m64n192k16.f32.bf16.bf16 {%0, %1, %2, %3, %4, %5, %6, %7, %8, %9, %10, %11, %12, %13, %14, %15, %16, %17, %18, %19, %20, %21, %22, %23, %24, %25, %26, %27, %28, %29, %30, %31, %32, %33, %34, %35, %36, %37, %38, %39, %40, %41, %42, %43, %44, %45, %46, %47, %48, %49, %50, %51, %52, %53, %54, %55, %56, %57, %58, %59, %60, %61, %62, %63, %64, %65, %66, %67, %68, %69, %70, %71, %72, %73, %74, %75, %76, %77, %78, %79, %80, %81, %82, %83, %84, %85, %86, %87, %88, %89, %90, %91, %92, %93, %94, %95}, %96, %97, p, 1, 1, 0, 1;\n}\n"
    : "+f"(d[0]), "+f"(d[1]), "+f"(d[2]), "+f"(d[3]), "+f"(d[4]), "+f"(d[5]), "+f"(d[6]), "+f"(d[7]), "+f"(d[8]), "+f"(d[9]), "+f"(d[10]), "+f"(d[11]), "+f"(d[12]), "+f"(d[13]), "+f"(d[14]), "+f"(d[15]), "+f"(d[16]), "+f"(d[17]), "+f"(d[18]), "+f"(d[19]), "+f"(d[20]), "+f"(d[21]), "+f"(d[22]), "+f"(d[23]), "+f"(d[24]), "+f"(d[25]), "+f"(d[26]), "+f"(d[27]), "+f"(d[28]), "+f"(d[29]), "+f"(d[30]), "+f"(d[31]), "+f"(d[32]), "+f"(d[33]), "+f"(d[34]), "+f"(d[35]), "+f"(d[36]), "+f"(d[37]), "+f"(d[38]), "+f"(d[39]), "+f"(d[40]), "+f"(d[41]), "+f"(d[42]), "+f"(d[43]), "+f"(d[44]), "+f"(d[45]), "+f"(d[46]), "+f"(d[47]), "+f"(d[48]), "+f"(d[49]), "+f"(d[50]), "+f"(d[51]), "+f"(d[52]), "+f"(d[53]), "+f"(d[54]), "+f"(d[55]), "+f"(d[56]), "+f"(d[57]), "+f"(d[58]), "+f"(d[59]), "+f"(d[60]), "+f"(d[61]), "+f"(d[62]), "+f"(d[63]), "+f"(d[64]), "+f"(d[65]), "+f"(d[66]), "+f"(d[67]), "+f"(d[68]), "+f"(d[69]), "+f"(d[70]), "+f"(d[71]), "+f"(d[72]), "+f"(d[73]), "+f"(d[74]), "+f"(d[75]), "+f"(d[76]), "+f"(d[77]), "+f"(d[78]), "+f"(d[79]), "+f"(d[80]), "+f"(d[81]), "+f"(d[82]), "+f"(d[83]), "+f"(d[84]), "+f"(d[85]), "+f"(d[86]), "+f"(d[87]), "+f"(d[88]), "+f"(d[89]), "+f"(d[90]), "+f"(d[91]), "+f"(d[92]), "+f"(d[93]), "+f"(d[94]), "+f"(d[95])
    : "l"(da), "l"(db), "r"(scale_d));
}

__device__ __forceinline__ void wgmma_n256(float (&d)[128], uint64_t da, uint64_t db, int scale_d) {
  asm volatile("{\n.reg .pred p;\nsetp.ne.b32 p, %130, 0;\n"
    "wgmma.mma_async.sync.aligned.m64n256k16.f32.bf16.bf16 {%0, %1, %2, %3, %4, %5, %6, %7, %8, %9, %10, %11, %12, %13, %14, %15, %16, %17, %18, %19, %20, %21, %22, %23, %24, %25, %26, %27, %28, %29, %30, %31, %32, %33, %34, %35, %36, %37, %38, %39, %40, %41, %42, %43, %44, %45, %46, %47, %48, %49, %50, %51, %52, %53, %54, %55, %56, %57, %58, %59, %60, %61, %62, %63, %64, %65, %66, %67, %68, %69, %70, %71, %72, %73, %74, %75, %76, %77, %78, %79, %80, %81, %82, %83, %84, %85, %86, %87, %88, %89, %90, %91, %92, %93, %94, %95, %96, %97, %98, %99, %100, %101, %102, %103, %104, %105, %106, %107, %108, %109, %110, %111, %112, %113, %114, %115, %116, %117, %118, %119, %120, %121, %122, %123, %124, %125, %126, %127}, %128, %129, p, 1, 1, 0, 1;\n}\n"
    : "+f"(d[0]), "+f"(d[1]), "+f"(d[2]), "+f"(d[3]), "+f"(d[4]), "+f"(d[5]), "+f"(d[6]), "+f"(d[7]), "+f"(d[8]), "+f"(d[9]), "+f"(d[10]), "+f"(d[11]), "+f"(d[12]), "+f"(d[13]), "+f"(d[14]), "+f"(d[15]), "+f"(d[16]), "+f"(d[17]), "+f"(d[18]), "+f"(d[19]), "+f"(d[20]), "+f"(d[21]), "+f"(d[22]), "+f"(d[23]), "+f"(d[24]), "+f"(d[25]), "+f"(d[26]), "+f"(d[27]), "+f"(d[28]), "+f"(d[29]), "+f"(d[30]), "+f"(d[31]), "+f"(d[32]), "+f"(d[33]), "+f"(d[34]), "+f"(d[35]), "+f"(d[36]), "+f"(d[37]), "+f"(d[38]), "+f"(d[39]), "+f"(d[40]), "+f"(d[41]), "+f"(d[42]), "+f"(d[43]), "+f"(d[44]), "+f"(d[45]), "+f"(d[46]), "+f"(d[47]), "+f"(d[48]), "+f"(d[49]), "+f"(d[50]), "+f"(d[51]), "+f"(d[52]), "+f"(d[53]), "+f"(d[54]), "+f"(d[55]), "+f"(d[56]), "+f"(d[57]), "+f"(d[58]), "+f"(d[59]), "+f"(d[60]), "+f"(d[61]), "+f"(d[62]), "+f"(d[63]), "+f"(d[64]), "+f"(d[65]), "+f"(d[66]), "+f"(d[67]), "+f"(d[68]), "+f"(d[69]), "+f"(d[70]), "+f"(d[71]), "+f"(d[72]), "+f"(d[73]), "+f"(d[74]), "+f"(d[75]), "+f"(d[76]), "+f"(d[77]), "+f"(d[78]), "+f"(d[79]), "+f"(d[80]), "+f"(d[81]), "+f"(d[82]), "+f"(d[83]), "+f"(d[84]), "+f"(d[85]), "+f"(d[86]), "+f"(d[87]), "+f"(d[88]), "+f"(d[89]), "+f"(d[90]), "+f"(d[91]), "+f"(d[92]), "+f"(d[93]), "+f"(d[94]), "+f"(d[95]), "+f"(d[96]), "+f"(d[97]), "+f"(d[98]), "+f"(d[99]), "+f"(d[100]), "+f"(d[101]), "+f"(d[102]), "+f"(d[103]), "+f"(d[104]), "+f"(d[105]), "+f"(d[106]), "+f"(d[107]), "+f"(d[108]), "+f"(d[109]), "+f"(d[110]), "+f"(d[111]), "+f"(d[112]), "+f"(d[113]), "+f"(d[114]), "+f"(d[115]), "+f"(d[116]), "+f"(d[117]), "+f"(d[118]), "+f"(d[119]), "+f"(d[120]), "+f"(d[121]), "+f"(d[122]), "+f"(d[123]), "+f"(d[124]), "+f"(d[125]), "+f"(d[126]), "+f"(d[127])
    : "l"(da), "l"(db), "r"(scale_d));
}

__device__ __forceinline__ void wgmma_rs_n128(float (&d)[64], const uint32_t (&a)[4], uint64_t db) {
  asm volatile(
    "wgmma.mma_async.sync.aligned.m64n128k16.f32.bf16.bf16 {%0, %1, %2, %3, %4, %5, %6, %7, %8, %9, %10, %11, %12, %13, %14, %15, %16, %17, %18, %19, %20, %21, %22, %23, %24, %25, %26, %27, %28, %29, %30, %31, %32, %33, %34, %35, %36, %37, %38, %39, %40, %41, %42, %43, %44, %45, %46, %47, %48, %49, %50, %51, %52, %53, %54, %55, %56, %57, %58, %59, %60, %61, %62, %63}, {%64, %65, %66, %67}, %68, 1, 1, 1, 1;\n"
    : "+f"(d[0]), "+f"(d[1]), "+f"(d[2]), "+f"(d[3]), "+f"(d[4]), "+f"(d[5]), "+f"(d[6]), "+f"(d[7]), "+f"(d[8]), "+f"(d[9]), "+f"(d[10]), "+f"(d[11]), "+f"(d[12]), "+f"(d[13]), "+f"(d[14]), "+f"(d[15]), "+f"(d[16]), "+f"(d[17]), "+f"(d[18]), "+f"(d[19]), "+f"(d[20]), "+f"(d[21]), "+f"(d[22]), "+f"(d[23]), "+f"(d[24]), "+f"(d[25]), "+f"(d[26]), "+f"(d[27]), "+f"(d[28]), "+f"(d[29]), "+f"(d[30]), "+f"(d[31]), "+f"(d[32]), "+f"(d[33]), "+f"(d[34]), "+f"(d[35]), "+f"(d[36]), "+f"(d[37]), "+f"(d[38]), "+f"(d[39]), "+f"(d[40]), "+f"(d[41]), "+f"(d[42]), "+f"(d[43]), "+f"(d[44]), "+f"(d[45]), "+f"(d[46]), "+f"(d[47]), "+f"(d[48]), "+f"(d[49]), "+f"(d[50]), "+f"(d[51]), "+f"(d[52]), "+f"(d[53]), "+f"(d[54]), "+f"(d[55]), "+f"(d[56]), "+f"(d[57]), "+f"(d[58]), "+f"(d[59]), "+f"(d[60]), "+f"(d[61]), "+f"(d[62]), "+f"(d[63])
    : "r"(a[0]), "r"(a[1]), "r"(a[2]), "r"(a[3]), "l"(db));
}

__device__ __forceinline__ void wgmma_rs_n192(float (&d)[96], const uint32_t (&a)[4], uint64_t db) {
  asm volatile(
    "wgmma.mma_async.sync.aligned.m64n192k16.f32.bf16.bf16 {%0, %1, %2, %3, %4, %5, %6, %7, %8, %9, %10, %11, %12, %13, %14, %15, %16, %17, %18, %19, %20, %21, %22, %23, %24, %25, %26, %27, %28, %29, %30, %31, %32, %33, %34, %35, %36, %37, %38, %39, %40, %41, %42, %43, %44, %45, %46, %47, %48, %49, %50, %51, %52, %53, %54, %55, %56, %57, %58, %59, %60, %61, %62, %63, %64, %65, %66, %67, %68, %69, %70, %71, %72, %73, %74, %75, %76, %77, %78, %79, %80, %81, %82, %83, %84, %85, %86, %87, %88, %89, %90, %91, %92, %93, %94, %95}, {%96, %97, %98, %99}, %100, 1, 1, 1, 1;\n"
    : "+f"(d[0]), "+f"(d[1]), "+f"(d[2]), "+f"(d[3]), "+f"(d[4]), "+f"(d[5]), "+f"(d[6]), "+f"(d[7]), "+f"(d[8]), "+f"(d[9]), "+f"(d[10]), "+f"(d[11]), "+f"(d[12]), "+f"(d[13]), "+f"(d[14]), "+f"(d[15]), "+f"(d[16]), "+f"(d[17]), "+f"(d[18]), "+f"(d[19]), "+f"(d[20]), "+f"(d[21]), "+f"(d[22]), "+f"(d[23]), "+f"(d[24]), "+f"(d[25]), "+f"(d[26]), "+f"(d[27]), "+f"(d[28]), "+f"(d[29]), "+f"(d[30]), "+f"(d[31]), "+f"(d[32]), "+f"(d[33]), "+f"(d[34]), "+f"(d[35]), "+f"(d[36]), "+f"(d[37]), "+f"(d[38]), "+f"(d[39]), "+f"(d[40]), "+f"(d[41]), "+f"(d[42]), "+f"(d[43]), "+f"(d[44]), "+f"(d[45]), "+f"(d[46]), "+f"(d[47]), "+f"(d[48]), "+f"(d[49]), "+f"(d[50]), "+f"(d[51]), "+f"(d[52]), "+f"(d[53]), "+f"(d[54]), "+f"(d[55]), "+f"(d[56]), "+f"(d[57]), "+f"(d[58]), "+f"(d[59]), "+f"(d[60]), "+f"(d[61]), "+f"(d[62]), "+f"(d[63]), "+f"(d[64]), "+f"(d[65]), "+f"(d[66]), "+f"(d[67]), "+f"(d[68]), "+f"(d[69]), "+f"(d[70]), "+f"(d[71]), "+f"(d[72]), "+f"(d[73]), "+f"(d[74]), "+f"(d[75]), "+f"(d[76]), "+f"(d[77]), "+f"(d[78]), "+f"(d[79]), "+f"(d[80]), "+f"(d[81]), "+f"(d[82]), "+f"(d[83]), "+f"(d[84]), "+f"(d[85]), "+f"(d[86]), "+f"(d[87]), "+f"(d[88]), "+f"(d[89]), "+f"(d[90]), "+f"(d[91]), "+f"(d[92]), "+f"(d[93]), "+f"(d[94]), "+f"(d[95])
    : "r"(a[0]), "r"(a[1]), "r"(a[2]), "r"(a[3]), "l"(db));
}

__device__ __forceinline__ void wgmma_rs_n256(float (&d)[128], const uint32_t (&a)[4], uint64_t db) {
  asm volatile(
    "wgmma.mma_async.sync.aligned.m64n256k16.f32.bf16.bf16 {%0, %1, %2, %3, %4, %5, %6, %7, %8, %9, %10, %11, %12, %13, %14, %15, %16, %17, %18, %19, %20, %21, %22, %23, %24, %25, %26, %27, %28, %29, %30, %31, %32, %33, %34, %35, %36, %37, %38, %39, %40, %41, %42, %43, %44, %45, %46, %47, %48, %49, %50, %51, %52, %53, %54, %55, %56, %57, %58, %59, %60, %61, %62, %63, %64, %65, %66, %67, %68, %69, %70, %71, %72, %73, %74, %75, %76, %77, %78, %79, %80, %81, %82, %83, %84, %85, %86, %87, %88, %89, %90, %91, %92, %93, %94, %95, %96, %97, %98, %99, %100, %101, %102, %103, %104, %105, %106, %107, %108, %109, %110, %111, %112, %113, %114, %115, %116, %117, %118, %119, %120, %121, %122, %123, %124, %125, %126, %127}, {%128, %129, %130, %131}, %132, 1, 1, 1, 1;\n"
    : "+f"(d[0]), "+f"(d[1]), "+f"(d[2]), "+f"(d[3]), "+f"(d[4]), "+f"(d[5]), "+f"(d[6]), "+f"(d[7]), "+f"(d[8]), "+f"(d[9]), "+f"(d[10]), "+f"(d[11]), "+f"(d[12]), "+f"(d[13]), "+f"(d[14]), "+f"(d[15]), "+f"(d[16]), "+f"(d[17]), "+f"(d[18]), "+f"(d[19]), "+f"(d[20]), "+f"(d[21]), "+f"(d[22]), "+f"(d[23]), "+f"(d[24]), "+f"(d[25]), "+f"(d[26]), "+f"(d[27]), "+f"(d[28]), "+f"(d[29]), "+f"(d[30]), "+f"(d[31]), "+f"(d[32]), "+f"(d[33]), "+f"(d[34]), "+f"(d[35]), "+f"(d[36]), "+f"(d[37]), "+f"(d[38]), "+f"(d[39]), "+f"(d[40]), "+f"(d[41]), "+f"(d[42]), "+f"(d[43]), "+f"(d[44]), "+f"(d[45]), "+f"(d[46]), "+f"(d[47]), "+f"(d[48]), "+f"(d[49]), "+f"(d[50]), "+f"(d[51]), "+f"(d[52]), "+f"(d[53]), "+f"(d[54]), "+f"(d[55]), "+f"(d[56]), "+f"(d[57]), "+f"(d[58]), "+f"(d[59]), "+f"(d[60]), "+f"(d[61]), "+f"(d[62]), "+f"(d[63]), "+f"(d[64]), "+f"(d[65]), "+f"(d[66]), "+f"(d[67]), "+f"(d[68]), "+f"(d[69]), "+f"(d[70]), "+f"(d[71]), "+f"(d[72]), "+f"(d[73]), "+f"(d[74]), "+f"(d[75]), "+f"(d[76]), "+f"(d[77]), "+f"(d[78]), "+f"(d[79]), "+f"(d[80]), "+f"(d[81]), "+f"(d[82]), "+f"(d[83]), "+f"(d[84]), "+f"(d[85]), "+f"(d[86]), "+f"(d[87]), "+f"(d[88]), "+f"(d[89]), "+f"(d[90]), "+f"(d[91]), "+f"(d[92]), "+f"(d[93]), "+f"(d[94]), "+f"(d[95]), "+f"(d[96]), "+f"(d[97]), "+f"(d[98]), "+f"(d[99]), "+f"(d[100]), "+f"(d[101]), "+f"(d[102]), "+f"(d[103]), "+f"(d[104]), "+f"(d[105]), "+f"(d[106]), "+f"(d[107]), "+f"(d[108]), "+f"(d[109]), "+f"(d[110]), "+f"(d[111]), "+f"(d[112]), "+f"(d[113]), "+f"(d[114]), "+f"(d[115]), "+f"(d[116]), "+f"(d[117]), "+f"(d[118]), "+f"(d[119]), "+f"(d[120]), "+f"(d[121]), "+f"(d[122]), "+f"(d[123]), "+f"(d[124]), "+f"(d[125]), "+f"(d[126]), "+f"(d[127])
    : "r"(a[0]), "r"(a[1]), "r"(a[2]), "r"(a[3]), "l"(db));
}

__device__ __forceinline__ uint32_t smem_u32(const void* p) { return (uint32_t)__cvta_generic_to_shared(p); }
__device__ __forceinline__ void mbar_init(uint32_t a, uint32_t cnt) { asm volatile("mbarrier.init.shared::cta.b64 [%0], %1;" ::"r"(a), "r"(cnt)); }
__device__ __forceinline__ void mbar_expect_tx(uint32_t a, uint32_t bytes) {
  asm volatile("mbarrier.arrive.expect_tx.shared::cta.b64 _, [%0], %1;" ::"r"(a), "r"(bytes) : "memory");
}
__device__ __forceinline__ void mbar_arrive_cluster(uint32_t a, uint32_t cta) {
  asm volatile("{\n.reg .b32 ra;\nmapa.shared::cluster.u32 ra, %0, %1;\nmbarrier.arrive.shared::cluster.b64 _, [ra];\n}\n" ::"r"(a), "r"(cta) : "memory");
}
__device__ __forceinline__ void mbar_arrive_both(uint32_t a) {
  mbar_arrive_cluster(a, 0); mbar_arrive_cluster(a, 1);
}
__device__ __forceinline__ void mbar_wait(uint32_t a, uint32_t parity, int code) {
  uint32_t ok = 0;
#pragma unroll 1
  for (uint32_t it = 0; it < SPIN_MAX; ++it) {
    asm volatile("{\n.reg .pred p;\nmbarrier.try_wait.parity.shared::cta.b64 p, [%1], %2;\nselp.u32 %0, 1, 0, p;\n}\n" : "=r"(ok) : "r"(a), "r"(parity) : "memory");
    if (ok) return;
  }
  FAIL(code);
}
__device__ __forceinline__ bool mbar_test(uint32_t a, uint32_t parity) {
  uint32_t ok;
  asm volatile("{\n.reg .pred p;\nmbarrier.test_wait.parity.shared::cta.b64 p, [%1], %2;\nselp.u32 %0, 1, 0, p;\n}\n" : "=r"(ok) : "r"(a), "r"(parity) : "memory");
  return __all_sync(0xffffffffu, ok != 0);
}
__device__ __forceinline__ void tma_load_2d(uint32_t dst, const CUtensorMap* map, int c0, int c1, uint32_t mbar) {
  asm volatile("cp.async.bulk.tensor.2d.shared::cluster.global.mbarrier::complete_tx::bytes [%0], [%1, {%3, %4}], [%2];" ::"r"(dst), "l"(map), "r"(mbar), "r"(c0), "r"(c1) : "memory");
}
__device__ __forceinline__ void tma_load_2d_mc(uint32_t dst, const CUtensorMap* map, int c0, int c1, uint32_t mbar, uint16_t mask) {
  asm volatile("cp.async.bulk.tensor.2d.shared::cluster.global.mbarrier::complete_tx::bytes.multicast::cluster [%0], [%1, {%3, %4}], [%2], %5;" ::"r"(dst), "l"(map), "r"(mbar), "r"(c0), "r"(c1), "h"(mask) : "memory");
}
__device__ __forceinline__ void tma_load_3d_mc(uint32_t dst, const CUtensorMap* map, int c0, int c1, int c2, uint32_t mbar, uint16_t mask) {
  asm volatile("cp.async.bulk.tensor.3d.shared::cluster.global.mbarrier::complete_tx::bytes.multicast::cluster [%0], [%1, {%3, %4, %5}], [%2], %6;" ::"r"(dst), "l"(map), "r"(mbar), "r"(c0), "r"(c1), "r"(c2), "h"(mask) : "memory");
}
__device__ __forceinline__ void tma_prefetch_3d(const CUtensorMap* map, int c0, int c1, int c2) {
  asm volatile("cp.async.bulk.prefetch.tensor.3d.L2.global.tile [%0, {%1, %2, %3}];" ::"l"(map), "r"(c0), "r"(c1), "r"(c2) : "memory");
}
__device__ __forceinline__ void wgmma_fence() { asm volatile("wgmma.fence.sync.aligned;" ::: "memory"); }
__device__ __forceinline__ void wgmma_commit() { asm volatile("wgmma.commit_group.sync.aligned;" ::: "memory"); }
template <int N> __device__ __forceinline__ void wgmma_wait() { asm volatile("wgmma.wait_group.sync.aligned %0;" ::"n"(N) : "memory"); }
__device__ __forceinline__ uint64_t make_desc(uint32_t saddr, uint32_t lbo, uint32_t sbo) {
  return (uint64_t)((saddr & 0x3FFFF) >> 4) | ((uint64_t)(lbo >> 4) << 16) | ((uint64_t)(sbo >> 4) << 32) | (1ull << 62);
}
__device__ __forceinline__ void fence_proxy_async() { asm volatile("fence.proxy.async.global;" ::: "memory"); }
__device__ __forceinline__ void named_bar(int id, int n) { asm volatile("bar.sync %0, %1;" ::"r"(id), "r"(n) : "memory"); }
__device__ __forceinline__ void cluster_sync() {
  asm volatile("barrier.cluster.arrive.release.aligned;\nbarrier.cluster.wait.acquire.aligned;" ::: "memory");
}
__device__ __forceinline__ unsigned ld_acquire(const unsigned* p) {
  unsigned v;
  asm volatile("ld.acquire.gpu.global.u32 %0, [%1];" : "=r"(v) : "l"(p) : "memory");
  return v;
}
__device__ __forceinline__ unsigned flag_wait(const unsigned* p, unsigned target, int code) {
#pragma unroll 1
  for (uint32_t it = 0; it < SPIN_MAX; ++it) {
    unsigned v = ld_acquire(p);
    if (v >= target) return v;
    __nanosleep(20);
  }
  FAIL(code);
  return 0;
}
__device__ __forceinline__ void flag_add(unsigned* p) {
  asm volatile("red.release.gpu.global.add.u32 [%0], 1;" ::"l"(p) : "memory");
}
__device__ __forceinline__ void agent_exit() {
  __threadfence();
  unsigned old = atomicAdd(&g_flags[272], 1u);
  if (old == NAGENTS - 1) {
    for (int i = 0; i < 273; ++i) g_flags[i] = 0;
    __threadfence();
  }
}
__device__ __forceinline__ float bf16r(float v) { return __bfloat162float(__float2bfloat16_rn(v)); }
__device__ __forceinline__ uint32_t pack_bf16(float lo, float hi) {
  uint32_t r;
  asm("cvt.rn.bf16x2.f32 %0, %1, %2;" : "=r"(r) : "f"(hi), "f"(lo));
  return r;
}
__device__ __forceinline__ void quad_transpose(uint32_t& v0, uint32_t& v1, uint32_t& v2, uint32_t& v3, int q) {
  bool b0 = q & 1;
  uint32_t s0 = b0 ? v0 : v1, s1 = b0 ? v2 : v3;
  s0 = __shfl_xor_sync(0xffffffffu, s0, 1);
  s1 = __shfl_xor_sync(0xffffffffu, s1, 1);
  if (b0) { v0 = s0; v2 = s1; } else { v1 = s0; v3 = s1; }
  bool b1 = q & 2;
  s0 = b1 ? v0 : v2; s1 = b1 ? v1 : v3;
  s0 = __shfl_xor_sync(0xffffffffu, s0, 2);
  s1 = __shfl_xor_sync(0xffffffffu, s1, 2);
  if (b1) { v0 = s0; v1 = s1; } else { v2 = s0; v3 = s1; }
}

struct Tile { int is_h; int col; int nb; };
__device__ __forceinline__ int num_tiles(int j) { return j ? 6 : 5; }
__device__ __forceinline__ Tile get_tile(int p, int j, int t) {
  Tile T;
  if (t == 0) {
    T.is_h = 0;
    if (j == 0) { T.col = 256 * p; T.nb = 4; }
    else { T.col = 1024 + 192 * p; T.nb = (p == 3) ? 2 : 3; }
  } else {
    T.is_h = 1; T.col = 128 * (9 * p + (j ? 4 : 0) + (t - 1)); T.nb = 4;
  }
  return T;
}

template <int NB> struct Acc { float a[NB * 32]; };
template <int NB> __device__ __forceinline__ void wgmma_nb(float (&d)[NB * 32], uint64_t da, uint64_t db, int sc);
template <> __device__ __forceinline__ void wgmma_nb<2>(float (&d)[64], uint64_t da, uint64_t db, int sc) { wgmma_n128(d, da, db, sc); }
template <> __device__ __forceinline__ void wgmma_nb<3>(float (&d)[96], uint64_t da, uint64_t db, int sc) { wgmma_n192(d, da, db, sc); }
template <> __device__ __forceinline__ void wgmma_nb<4>(float (&d)[128], uint64_t da, uint64_t db, int sc) { wgmma_n256(d, da, db, sc); }
template <int NB> __device__ __forceinline__ void wgmma_rs_nb(float (&d)[NB * 32], const uint32_t (&a)[4], uint64_t db);
template <> __device__ __forceinline__ void wgmma_rs_nb<2>(float (&d)[64], const uint32_t (&a)[4], uint64_t db) { wgmma_rs_n128(d, a, db); }
template <> __device__ __forceinline__ void wgmma_rs_nb<3>(float (&d)[96], const uint32_t (&a)[4], uint64_t db) { wgmma_rs_n192(d, a, db); }
template <> __device__ __forceinline__ void wgmma_rs_nb<4>(float (&d)[128], const uint32_t (&a)[4], uint64_t db) { wgmma_rs_n256(d, a, db); }

struct Ctx {
  uint32_t sbase;
  uint32_t full1, empty1, full2, empty2;
  uint32_t peer;
  int wg;
  int tid;
};

__device__ __forceinline__ void publish(unsigned* flag) {
  __threadfence();
  __syncwarp();
  if ((threadIdx.x & 31) == 0) flag_add(flag);
}
template <int NB>
__device__ __forceinline__ void g1_tile(const Ctx& c, float (&acc)[NB * 32], uint32_t& it  , const uint32_t (&areg)[8][4]) {
  const uint32_t abase = c.sbase + c.wg * 8192;
  wgmma_fence();
#pragma unroll 1
  for (int kb = 0; kb < 14; ++kb) {
    uint32_t s = it % NS1, ph = (it / NS1) & 1;
    mbar_wait(c.full1 + 8 * s, ph, 0);
    uint32_t a0 = abase + (kb >> 1) * 16384 + (kb & 1) * 64;
    uint32_t b0 = c.sbase + slot1_off(s);
    wgmma_fence();
    wgmma_nb<NB>(acc, make_desc(a0, 16, 1024), make_desc(b0, 4096, 1024), kb > 0);
    wgmma_nb<NB>(acc, make_desc(a0 + 32, 16, 1024), make_desc(b0 + 2048, 4096, 1024), 1);
    wgmma_commit();
    if (kb > 0) {
      wgmma_wait<1>();
      if (c.tid == 0) mbar_arrive_both(c.empty1 + 8 * ((it - 1) % NS1));
    }
    ++it;
  }
#pragma unroll
  for (int kk = 0; kk < 4; ++kk) {
    uint32_t s = it % NS1, ph = (it / NS1) & 1;
    mbar_wait(c.full1 + 8 * s, ph, 0);
    uint32_t b0 = c.sbase + slot1_off(s);
    wgmma_fence();
    wgmma_rs_nb<NB>(acc, areg[2 * kk], make_desc(b0, 4096, 1024));
    wgmma_rs_nb<NB>(acc, areg[2 * kk + 1], make_desc(b0 + 2048, 4096, 1024));
    wgmma_commit();
    wgmma_wait<1>();
    if (c.tid == 0) mbar_arrive_both(c.empty1 + 8 * ((it - 1) % NS1));
    ++it;
  }
  wgmma_wait<0>();
  if (c.tid == 0) mbar_arrive_both(c.empty1 + 8 * ((it - 1) % NS1));
}

template <int NB>
__device__ __forceinline__ void epi_h(const Ctx& c, float (&acc)[NB * 32], int row0  , int hcol) {
  constexpr int G = NB * 4;
  const int lane = c.tid & 31, w = c.tid >> 5, q = lane & 3;
  const int r = row0 + c.wg * 64 + w * 16 + (lane >> 2);
  __nv_bfloat16* dst0 = g_act + (size_t)r * ACT_ + 576 + hcol + q * 8;
  __nv_bfloat16* dst1 = dst0 + 8 * ACT_;
  const __nv_bfloat162 zero2 = __floats2bfloat162_rn(0.f, 0.f);
#pragma unroll
  for (int a = 0; a < G / 4; ++a) {
    uint32_t v[4], u[4];
#pragma unroll
    for (int i = 0; i < 4; ++i) {
      int g = 4 * a + i;
      uint32_t g0 = pack_bf16(acc[4 * g], acc[4 * g + 1]), g1 = pack_bf16(acc[4 * g + 2], acc[4 * g + 3]);
      uint32_t u0 = pack_bf16(acc[4 * (g + G)], acc[4 * (g + G) + 1]), u1 = pack_bf16(acc[4 * (g + G) + 2], acc[4 * (g + G) + 3]);
      __nv_bfloat162 h0 = __hmul2(__hmax2(*(__nv_bfloat162*)&g0, zero2), *(__nv_bfloat162*)&u0);
      __nv_bfloat162 h1 = __hmul2(__hmax2(*(__nv_bfloat162*)&g1, zero2), *(__nv_bfloat162*)&u1);
      v[i] = *(uint32_t*)&h0; u[i] = *(uint32_t*)&h1;
    }
    quad_transpose(v[0], v[1], v[2], v[3], q);
    quad_transpose(u[0], u[1], u[2], u[3], q);
    *(uint4*)(dst0 + a * 32) = make_uint4(v[0], v[1], v[2], v[3]);
    *(uint4*)(dst1 + a * 32) = make_uint4(u[0], u[1], u[2], u[3]);
  }
}
template <int NB>
__device__ __forceinline__ void epi_qkv(const Ctx& c, float (&acc)[NB * 32], int row0, int col) {
  constexpr int G = NB * 8;
  const int lane = c.tid & 31, w = c.tid >> 5, q = lane & 3;
  const int r = row0 + c.wg * 64 + w * 16 + (lane >> 2);
  __nv_bfloat16* dst0 = g_qkv + (size_t)r * QKV_ + col + q * 8;
  __nv_bfloat16* dst1 = dst0 + 8 * QKV_;
#pragma unroll
  for (int a = 0; a < G / 4; ++a) {
    uint32_t v[4], u[4];
#pragma unroll
    for (int i = 0; i < 4; ++i) {
      int g = 4 * a + i;
      v[i] = pack_bf16(acc[4 * g], acc[4 * g + 1]); u[i] = pack_bf16(acc[4 * g + 2], acc[4 * g + 3]);
    }
    quad_transpose(v[0], v[1], v[2], v[3], q);
    quad_transpose(u[0], u[1], u[2], u[3], q);
    *(uint4*)(dst0 + a * 32) = make_uint4(v[0], v[1], v[2], v[3]);
    *(uint4*)(dst1 + a * 32) = make_uint4(u[0], u[1], u[2], u[3]);
  }
}
__device__ __forceinline__ void mbar_arrive_local(uint32_t a) { asm volatile("mbarrier.arrive.shared::cta.b64 _, [%0];" ::"r"(a) : "memory"); }

template <int NA>
__device__ __forceinline__ void acc_to_smem(float (&acc)[NA], uint32_t a0  , uint32_t pitch) {
#pragma unroll
  for (int g = 0; g < NA / 4; ++g) {
    asm volatile("st.shared.v2.f32 [%0], {%1, %2};" ::"r"(a0 + g * 32), "f"(acc[4 * g]), "f"(acc[4 * g + 1]) : "memory");
    asm volatile("st.shared.v2.f32 [%0], {%1, %2};" ::"r"(a0 + 8 * pitch + g * 32), "f"(acc[4 * g + 2]), "f"(acc[4 * g + 3]) : "memory");
  }
}
__device__ __forceinline__ float4 lds128(uint32_t a) {
  float4 v;
  asm volatile("ld.shared.v4.f32 {%0, %1, %2, %3}, [%4];" : "=f"(v.x), "=f"(v.y), "=f"(v.z), "=f"(v.w) : "r"(a) : "memory");
  return v;
}

__device__ __forceinline__ void mma16816(float (&c)[4], uint32_t a0, uint32_t a1, uint32_t a2, uint32_t a3, uint32_t b0, uint32_t b1) {
  asm volatile("mma.sync.aligned.m16n8k16.row.col.f32.bf16.bf16.f32 {%0,%1,%2,%3}, {%4,%5,%6,%7}, {%8,%9}, {%0,%1,%2,%3};"
               : "+f"(c[0]), "+f"(c[1]), "+f"(c[2]), "+f"(c[3]) : "r"(a0), "r"(a1), "r"(a2), "r"(a3), "r"(b0), "r"(b1));
}
__device__ __forceinline__ uint32_t movm(uint32_t a) {
  uint32_t d;
  asm volatile("movmatrix.sync.aligned.m8n8.trans.b16 %0, %1;" : "=r"(d) : "r"(a));
  return d;
}
struct HeadRegs { uint32_t q[2][3], k[4][3], v[4][3]; };
__device__ __forceinline__ void load_head(HeadRegs& R, int h, int qrow, int g, int t) {
  const int o = h & 1;
  const int wp = 9 * h + o + 2 * t, wt = 9 * h + (o ? 0 : 8);
#pragma unroll
  for (int r = 0; r < 2; ++r) {
    const uint32_t* p = (const uint32_t*)(g_qkv + (size_t)(qrow + g + 8 * r) * QKV_);
    uint2 a = *(const uint2*)(p + wp);
    R.q[r][0] = a.x; R.q[r][1] = a.y; R.q[r][2] = t == 0 ? p[wt] : 0u;
  }
#pragma unroll
  for (int nt = 0; nt < 4; ++nt) {
    const int jj = 8 * nt + g, kr = qrow - 14 + jj;
    const bool ok = (kr >= 0) && (jj < 30);
    const uint32_t* p = (const uint32_t*)(g_qkv + (size_t)(ok ? kr : qrow) * QKV_);
    uint2 a = make_uint2(0u, 0u);
    if (ok) a = *(const uint2*)(p + 288 + wp);
    R.k[nt][0] = a.x; R.k[nt][1] = a.y; R.k[nt][2] = (ok && t == 0) ? p[288 + wt] : 0u;
    R.v[nt][0] = ok ? p[576 + 9 * h + t] : 0u; R.v[nt][1] = ok ? p[576 + 9 * h + 4 + t] : 0u;
    R.v[nt][2] = (ok && t == 0) ? p[576 + 9 * h + 8] : 0u;
  }
}
__device__ __noinline__ void attention(int row0, int role, int m, int aw, int lane) {
  if (lane < 8) flag_wait(&g_flags[m * 8 + lane], 1, 5);
  else if (lane < 16 && role == 0 && m > 0) flag_wait(&g_flags[(m - 1) * 8 + lane - 8], 1, 5);
  __syncwarp();
  if (aw == 0 && lane == 0) TS2(24);
  const float scale = 0.23570226039551584f;
  const int g = lane >> 2, t = lane & 3;
  const int qrow = row0 + role * 16;
  HeadRegs N;
  load_head(N, aw, qrow, g, t);
#pragma unroll 1
  for (int h = aw; h < 32; h += 8) {
    HeadRegs R = N;
    if (h + 8 < 32) load_head(N, h + 8, qrow, g, t);
    float sc[4][4];
#pragma unroll
    for (int nt = 0; nt < 4; ++nt) {
      sc[nt][0] = sc[nt][1] = sc[nt][2] = sc[nt][3] = 0.f;
      mma16816(sc[nt], R.q[0][0], R.q[1][0], R.q[0][1], R.q[1][1], R.k[nt][0], R.k[nt][1]);
      mma16816(sc[nt], R.q[0][2], R.q[1][2], 0u, 0u, R.k[nt][2], 0u);
    }
    const int par = g & 1;
    float l0[4], l1[4];
    float mx0 = -3.0e38f, mx1 = -3.0e38f;
#pragma unroll
    for (int nt = 0; nt < 4; ++nt) {
      const int jj = 8 * nt + 2 * t + par;
      const int d0 = g + 14 - jj, d1 = d0 + 8;
      const bool inr = qrow - 14 + jj >= 0;
      const bool ok0 = inr && d0 >= 0 && d0 <= 14, ok1 = inr && d1 >= 0 && d1 <= 14;
      uint32_t pk = pack_bf16(par ? sc[nt][1] : sc[nt][0], par ? sc[nt][3] : sc[nt][2]);
      pk = pack_bf16(__uint_as_float(pk << 16) * scale, __uint_as_float(pk & 0xffff0000u) * scale);
      l0[nt] = ok0 ? __uint_as_float(pk << 16) : -3.0e38f;
      l1[nt] = ok1 ? __uint_as_float(pk & 0xffff0000u) : -3.0e38f;
      mx0 = fmaxf(mx0, l0[nt]); mx1 = fmaxf(mx1, l1[nt]);
    }
    mx0 = fmaxf(mx0, __shfl_xor_sync(0xffffffffu, mx0, 1)); mx0 = fmaxf(mx0, __shfl_xor_sync(0xffffffffu, mx0, 2));
    mx1 = fmaxf(mx1, __shfl_xor_sync(0xffffffffu, mx1, 1)); mx1 = fmaxf(mx1, __shfl_xor_sync(0xffffffffu, mx1, 2));
    float s0 = 0.f, s1 = 0.f;
#pragma unroll
    for (int nt = 0; nt < 4; ++nt) {
      l0[nt] = __expf(l0[nt] - mx0); l1[nt] = __expf(l1[nt] - mx1);
      s0 += l0[nt]; s1 += l1[nt];
    }
    s0 += __shfl_xor_sync(0xffffffffu, s0, 1); s0 += __shfl_xor_sync(0xffffffffu, s0, 2);
    s1 += __shfl_xor_sync(0xffffffffu, s1, 1); s1 += __shfl_xor_sync(0xffffffffu, s1, 2);
    const float i0 = __frcp_rn(s0), i1 = __frcp_rn(s1);
    uint32_t pa[2][4];
#pragma unroll
    for (int nt = 0; nt < 4; ++nt) {
      const float p0 = l0[nt] * i0, p1 = l1[nt] * i1;
      pa[nt >> 1][(nt & 1) * 2] = par ? pack_bf16(0.f, p0) : pack_bf16(p0, 0.f);
      pa[nt >> 1][(nt & 1) * 2 + 1] = par ? pack_bf16(0.f, p1) : pack_bf16(p1, 0.f);
    }
    uint32_t* o0p = (uint32_t*)(g_act + (size_t)(qrow + g) * ACT_) + 9 * h;
    uint32_t* o1p = (uint32_t*)(g_act + (size_t)(qrow + g + 8) * ACT_) + 9 * h;
#pragma unroll
    for (int cg = 0; cg < 3; ++cg) {
      float oc[4] = {0.f, 0.f, 0.f, 0.f};
      mma16816(oc, pa[0][0], pa[0][1], pa[0][2], pa[0][3], movm(R.v[0][cg]), movm(R.v[1][cg]));
      mma16816(oc, pa[1][0], pa[1][1], pa[1][2], pa[1][3], movm(R.v[2][cg]), movm(R.v[3][cg]));
      if (cg < 2 || t == 0) {
        o0p[4 * cg + t] = pack_bf16(oc[0], oc[1]);
        o1p[4 * cg + t] = pack_bf16(oc[2], oc[3]);
      }
    }
  }
  if (aw == 0 && lane == 0) TS2(26);
}

__global__ void __cluster_dims__(2, 1, 1) __launch_bounds__(384, 1)
fused_kernel(const __grid_constant__ CUtensorMap m_qkv1, const __grid_constant__ CUtensorMap m_qkv2,
             const __grid_constant__ CUtensorMap m_gate2, const __grid_constant__ CUtensorMap m_up2,
             const __grid_constant__ CUtensorMap m_wo5, const __grid_constant__ CUtensorMap m_wo4,
             const __grid_constant__ CUtensorMap m_down5, const __grid_constant__ CUtensorMap m_down4,
             const __grid_constant__ CUtensorMap m_act,
             const __nv_bfloat16* __restrict__ x, __nv_bfloat16* __restrict__ out) {
  extern __shared__ uint8_t smem_raw[];
  const uint32_t sbase = (smem_u32(smem_raw) + 1023) & ~1023u;
  const uint32_t bars = sbase + DATA_BYTES;
  const uint32_t full1 = bars, empty1 = bars + 64, full2 = bars + 128, empty2 = bars + 192, pub = bars + 256;
  const int rank = blockIdx.x & 1, cl = blockIdx.x >> 1;
  const int role = cl & 7, m = (cl >> 3) * 2 + rank, p = role >> 1, j = role & 1;
  const int row0 = m * 128;
  const int warp = __shfl_sync(0xffffffffu, (int)(threadIdx.x >> 5), 0), lane = threadIdx.x & 31;
  const int nkb2 = (p == 3) ? 21 : 20;
  const int nblk2 = j ? 4 : 5;
  const int ncol0 = j ? 320 : 0;

  uint4 nx[9];
  if (warp >= 4) {
    const int cw = warp - 4;
    const uint4* src = (const uint4*)(x + (size_t)(row0 + cw * 16 + (lane >> 3)) * D_) + (lane & 7);
#pragma unroll
    for (int t = 0; t < 9; ++t) nx[t] = __ldg(src + 8 * t);
  }
  if (threadIdx.x == 0) {
    for (int s = 0; s < NS1; ++s) { mbar_init(full1 + 8 * s, 1); mbar_init(empty1 + 8 * s, MC ? 4 : 2); }
    for (int s = 0; s < NS2; ++s) { mbar_init(full2 + 8 * s, 1); mbar_init(empty2 + 8 * s, MC ? 4 : 2); }
    for (int s = 0; s < 7; ++s) mbar_init(pub + 8 * s, 256);
    asm volatile("fence.mbarrier_init.release.cluster;" ::: "memory");
  }
  __syncthreads();
  cluster_sync();

  if (warp < 4) {
    asm volatile("setmaxnreg.dec.sync.aligned.u32 40;");
    if (warp == 0) {
      if (lane == 0) {
        uint32_t it = 0;
        const int nt = num_tiles(j);
        volatile uint32_t* known = (volatile uint32_t*)(smem_raw + (bars + 320 - smem_u32(smem_raw)));
        volatile uint32_t* sched = known + 12;
        for (int t = 0; t < nt; ++t) {
          Tile T = get_tile(p, j, t);
          const CUtensorMap* mp; int cb, nmine;
          if (T.is_h) { mp = rank ? &m_up2 : &m_gate2; cb = T.col >> 6; nmine = 2; }
          else if (T.nb == 4) { mp = &m_qkv2; cb = (T.col >> 6) + 2 * rank; nmine = 2; }
          else if (T.nb == 3) { mp = rank ? &m_qkv1 : &m_qkv2; cb = (T.col >> 6) + 2 * rank; nmine = rank ? 1 : 2; }
          else { mp = &m_qkv1; cb = (T.col >> 6) + rank; nmine = 1; }
          const uint32_t doff = (T.nb == 2 ? rank : 2 * rank) * 4096;
          for (int kb = 0; kb < 18; ++kb, ++it) {
            uint32_t s = it % NS1, ph = (it / NS1) & 1;
            if (it == 5) {
              for (int r = 0; r < 9; ++r) known[r] = 0;
              const int hlo = p == 0 ? 0 : 20 * p - 9, hhi = 20 * p + 11 + (p == 3 ? 1 : 0);
              int n = 0;
              for (int tt = 1; tt <= 5; ++tt)
                for (int hb = hlo; hb < hhi; ++hb) {
                  int TT = hb >> 1, pp = TT / 9, idx = TT - 9 * pp;
                  int ot = 1 + (idx >= 4 ? idx - 4 : idx);
                  if (ot == tt) sched[n++] = (uint32_t)hb | ((uint32_t)(2 * pp + (idx >= 4)) << 8) | ((uint32_t)(ot + 1) << 16);
                }
            }
            mbar_wait(empty1 + 8 * s, s >= 5 ? ph : ph ^ 1, 1);
            mbar_expect_tx(full1 + 8 * s, T.nb * 4096);
            tma_load_3d_mc(sbase + slot1_off(s) + doff, mp, 0, kb * 32, cb, full1 + 8 * s, 3);
            (void)nmine;
          }
        }
        const CUtensorMap* mwo = j ? &m_wo4 : &m_wo5;
        const CUtensorMap* mdn = j ? &m_down4 : &m_down5;
        for (int i = 0; i < nkb2; ++i) {
          uint32_t s = i % NS2, ph = (i / NS2) & 1;
          int acol, kn, wrow; const CUtensorMap* mp; const unsigned* fl; unsigned tgt;
          if (p == 0 && i >= 11) {
            acol = (i - 11) * 64; mp = mwo; wrow = acol; fl = &g_flags[128 + m]; tgt = 8; kn = 8;
          } else {
            uint32_t e = sched[i];
            wrow = (e & 255) * 64; kn = (e >> 8) & 255; tgt = e >> 16;
            acol = 576 + wrow; mp = mdn; fl = &g_flags[m * 8 + kn];
          }
          mbar_wait(empty2 + 8 * s, ph, 2);
          mbar_expect_tx(full2 + 8 * s, 16384 + nblk2 * 8192);
          uint32_t dst = sbase + s * ST2_BYTES;
          tma_load_3d_mc(dst + 16384 + rank * nblk2 * 4096, mp, 0, wrow + 32 * rank, ncol0 >> 6, full2 + 8 * s, 3);
          if (known[kn] < tgt) { known[kn] = flag_wait(fl, tgt, 4); fence_proxy_async(); }
          tma_load_2d(dst, &m_act, acol, row0, full2 + 8 * s);
          TS2(32 + i);
        }
        agent_exit();
      }
    } else if (warp == 1) {
      const int nt = num_tiles(j);
      for (int t = 0; t < nt; ++t) {
        mbar_wait(pub + 8 * t, 0, 7);
        if (lane == 0) { if (t == 0) TS2(27); __threadfence(); flag_add(&g_flags[m * 8 + role]); if (t == 0) TS2(28); }
        __syncwarp();
        if (t == 1) {
          mbar_wait(pub + 8 * 6, 0, 7);
          if (lane == 0) { __threadfence(); flag_add(&g_flags[128 + m]); }
          __syncwarp();
        }
      }
      if (lane == 0) agent_exit();
    } else if (warp == 2) {
      if (lane == 0) {
        const int mp8 = cl >> 3, nt = num_tiles(j);
        for (int t = 1; t <= nt; ++t) {
          if (t >= 2) mbar_wait(pub + 8 * (t - 2), 0, 7);
          if (t < nt) {
            Tile T = get_tile(p, j, t);
            for (int kb = mp8; kb < 18; kb += 8) tma_prefetch_3d(rank ? &m_up2 : &m_gate2, 0, kb * 32, T.col >> 6);
          } else {
            const int hlo = p == 0 ? 0 : 20 * p - 9, hhi = 20 * p + 11 + (p == 3 ? 1 : 0);
            for (int hb = hlo + mp8; hb < hhi; hb += 8) tma_prefetch_3d(j ? &m_down4 : &m_down5, 0, hb * 64 + 32 * rank, ncol0 >> 6);
            if (p == 0) for (int ob = mp8; ob < 9; ob += 8) tma_prefetch_3d(j ? &m_wo4 : &m_wo5, 0, ob * 64 + 32 * rank, ncol0 >> 6);
          }
        }
      }
    }
  } else {
    asm volatile("setmaxnreg.inc.sync.aligned.u32 232;");
    Ctx c;
    c.sbase = sbase; c.full1 = full1; c.empty1 = empty1; c.full2 = full2; c.empty2 = empty2; c.peer = rank ^ 1;
    c.wg = (warp - 4) >> 2; c.tid = threadIdx.x - 128 - c.wg * 128;
    const int w = c.tid >> 5;
    if (c.wg == 0 && c.tid == 0) TS(0);
    uint32_t areg[8][4];
    {
      const int sub = lane >> 3, li = lane & 7;
#pragma unroll 1
      for (int itr = 0; itr < 4; ++itr) {
        const int r = c.wg * 64 + w * 16 + itr * 4 + sub;
        uint4 xv[9];
#pragma unroll
        for (int t = 0; t < 9; ++t) xv[t] = nx[t];
        if (itr < 3) {
          const uint4* src = (const uint4*)(x + (size_t)(row0 + r + 4) * D_) + li;
#pragma unroll
          for (int t = 0; t < 9; ++t) nx[t] = __ldg(src + 8 * t);
        }
        float s0 = 0.f, s1 = 0.f;
#pragma unroll
        for (int t = 0; t < 9; ++t) {
          const uint32_t* u = (const uint32_t*)&xv[t];
#pragma unroll
          for (int e = 0; e < 4; ++e) { s0 += __uint_as_float(u[e] << 16); s1 += __uint_as_float(u[e] & 0xffff0000u); }
        }
        float sum = s0 + s1;
        sum += __shfl_xor_sync(0xffffffffu, sum, 1); sum += __shfl_xor_sync(0xffffffffu, sum, 2); sum += __shfl_xor_sync(0xffffffffu, sum, 4);
        const float mean = sum * (1.f / 576.f);
        float q0 = 0.f, q1 = 0.f;
#pragma unroll
        for (int t = 0; t < 9; ++t) {
          const uint32_t* u = (const uint32_t*)&xv[t];
#pragma unroll
          for (int e = 0; e < 4; ++e) {
            float a = __uint_as_float(u[e] << 16) - mean, b = __uint_as_float(u[e] & 0xffff0000u) - mean;
            q0 = fmaf(a, a, q0); q1 = fmaf(b, b, q1);
          }
        }
        float sq = q0 + q1;
        sq += __shfl_xor_sync(0xffffffffu, sq, 1); sq += __shfl_xor_sync(0xffffffffu, sq, 2); sq += __shfl_xor_sync(0xffffffffu, sq, 4);
        const float vb = bf16r(sq * (1.f / 576.f));
        const float rinv = 1.f / bf16r(sqrtf(bf16r(vb + 1e-5f)));
        const __nv_bfloat162 mb2 = __float2bfloat162_rn(mean);
        const uint32_t dsta = sbase + r * 128 + ((li ^ (r & 7)) << 4);
#pragma unroll
        for (int t = 0; t < 9; ++t) {
          const uint32_t* u = (const uint32_t*)&xv[t];
          uint32_t o[4];
#pragma unroll
          for (int e = 0; e < 4; ++e) {
            __nv_bfloat162 d2 = __hsub2(*(const __nv_bfloat162*)&u[e], mb2);
            uint32_t du = *(uint32_t*)&d2;
            o[e] = pack_bf16(__uint_as_float(du << 16) * rinv, __uint_as_float(du & 0xffff0000u) * rinv);
          }
          asm volatile("st.shared.v4.b32 [%0], {%1, %2, %3, %4};" ::"r"(dsta + t * 16384), "r"(o[0]), "r"(o[1]), "r"(o[2]), "r"(o[3]) : "memory");
        }
      }
      asm volatile("fence.proxy.async.shared::cta;" ::: "memory");
      __syncwarp();
      {
        const int r = c.wg * 64 + w * 16 + (lane & 7) + ((lane >> 3) & 1) * 8;
        const int hi = lane >> 4;
#pragma unroll
        for (int ks = 0; ks < 8; ++ks) {
          const uint32_t ad = sbase + (7 + (ks >> 2)) * 16384 + r * 128 + ((((ks & 3) * 2 + hi) ^ (r & 7)) << 4);
          asm volatile("ldmatrix.sync.aligned.m8n8.x4.shared.b16 {%0, %1, %2, %3}, [%4];"
                       : "=r"(areg[ks][0]), "=r"(areg[ks][1]), "=r"(areg[ks][2]), "=r"(areg[ks][3]) : "r"(ad) : "memory");
        }
      }
      named_bar(1 + c.wg, 128);
      if (c.tid == 0) { mbar_arrive_both(empty1 + 8 * 5); mbar_arrive_both(empty1 + 8 * 6); }
      if (c.wg == 1) {
        const long long t0 = clock64();
        while (clock64() - t0 < SKEW) {}
      }
    }
    if (c.wg == 0 && c.tid == 0) TS(1);
    unsigned* myflag = &g_flags[m * 8 + role];
    {
      uint32_t it = 0;
      const int nt = num_tiles(j);
#pragma unroll 1
      for (int t = 0; t < nt; ++t) {
        Tile T = get_tile(p, j, t);
        if (T.nb == 4) {
          float acc[128] = {};
          g1_tile<4>(c, acc, it, areg);
          if (T.is_h) epi_h<4>(c, acc, row0, T.col); else epi_qkv<4>(c, acc, row0, T.col);
        } else if (T.nb == 3) {
          float acc[96] = {};
          g1_tile<3>(c, acc, it, areg);
          epi_qkv<3>(c, acc, row0, T.col);
        } else {
          float acc[64] = {};
          g1_tile<2>(c, acc, it, areg);
          epi_qkv<2>(c, acc, row0, T.col);
        }
        if (t == nt - 1 && c.tid == 0) {
          for (int s = 0; s < NS2; ++s) { mbar_arrive_both(empty2 + 8 * s); }
        }
        mbar_arrive_local(pub + 8 * t);
        if (t == 1) {
          if (c.wg == 0 && c.tid == 0) TS(11);
          attention(row0, role, m, c.wg * 4 + w, lane);
          mbar_arrive_local(pub + 8 * 6);
          if (c.wg == 0 && c.tid == 0) TS(12);
        }
        if (c.wg == 0 && c.tid == 0) TS(2 + t);
      }
    }
    const int nch = j ? 32 : 40;
    const uint32_t pitch = nch * 32 + 32;
    const uint32_t sacc = sbase + (c.wg * 64 + w * 16 + (lane >> 2)) * pitch + (lane & 3) * 8;
    if (j == 0) {
      float acc1[96] = {}, acc2[64] = {};
      wgmma_fence();
#pragma unroll 1
      for (int i = 0; i < nkb2; ++i) {
        uint32_t s = i % NS2, ph = (i / NS2) & 1;
        mbar_wait(full2 + 8 * s, ph, 3);
        if (c.wg == 0 && c.tid == 0) TS2(i);
        uint32_t a0 = sbase + s * ST2_BYTES + c.wg * 8192, b0 = sbase + s * ST2_BYTES + 16384;
        wgmma_fence();
#pragma unroll
        for (int k = 0; k < 4; ++k) {
          uint64_t da = make_desc(a0 + k * 32, 16, 1024);
          const uint32_t bk = b0 + (k >> 1) * (5 * 4096) + (k & 1) * 2048;
          wgmma_n192(acc1, da, make_desc(bk, 4096, 1024), (i | k) != 0);
          wgmma_n128(acc2, da, make_desc(bk + 3 * 4096, 4096, 1024), (i | k) != 0);
        }
        wgmma_commit();
        if (i > 0) {
          wgmma_wait<1>();
          if (c.tid == 0 && i - 1 + NS2 < nkb2) { uint32_t sp = (i - 1) % NS2; mbar_arrive_both(empty2 + 8 * sp); }
        }
      }
      wgmma_wait<0>();
      if (c.wg == 0 && c.tid == 0) TS(8);
      named_bar(3, 256);
      acc_to_smem<96>(acc1, sacc, pitch);
      acc_to_smem<64>(acc2, sacc + 768, pitch);
    } else {
      float acc[128] = {};
      wgmma_fence();
#pragma unroll 1
      for (int i = 0; i < nkb2; ++i) {
        uint32_t s = i % NS2, ph = (i / NS2) & 1;
        mbar_wait(full2 + 8 * s, ph, 3);
        if (c.wg == 0 && c.tid == 0) TS2(i);
        uint32_t a0 = sbase + s * ST2_BYTES + c.wg * 8192, b0 = sbase + s * ST2_BYTES + 16384;
        wgmma_fence();
#pragma unroll
        for (int k = 0; k < 4; ++k)
          wgmma_n256(acc, make_desc(a0 + k * 32, 16, 1024), make_desc(b0 + (k >> 1) * (4 * 4096) + (k & 1) * 2048, 4096, 1024), (i | k) != 0);
        wgmma_commit();
        if (i > 0) {
          wgmma_wait<1>();
          if (c.tid == 0 && i - 1 + NS2 < nkb2) { uint32_t sp = (i - 1) % NS2; mbar_arrive_both(empty2 + 8 * sp); }
        }
      }
      wgmma_wait<0>();
      if (c.wg == 0 && c.tid == 0) TS(8);
      named_bar(3, 256);
      acc_to_smem<128>(acc, sacc, pitch);
    }
    named_bar(3, 256);
    if (c.wg == 0 && c.tid == 0) TS2(60);
    {
      const int t256 = c.wg * 128 + c.tid;
      uint4* xs = g_xch + (size_t)((m * 2 + j) * 4) * 128 * 40;
      unsigned* pf = &g_flags[144 + (m * 2 + j) * 4];
      const uint8_t* sgen = smem_raw + (sbase - smem_u32(smem_raw));
#pragma unroll 5
      for (int e = t256; e < 96 * nch; e += 256) {
        int r = e / nch, cI = e - r * nch;
        r += (r >= 32 * p) ? 32 : 0;
        const float4 u0 = *(const float4*)(sgen + r * pitch + cI * 32), u1 = *(const float4*)(sgen + r * pitch + cI * 32 + 16);
        xs[((size_t)p * 128 + r) * 40 + cI] = make_uint4(pack_bf16(u0.x, u0.y), pack_bf16(u0.z, u0.w), pack_bf16(u1.x, u1.y), pack_bf16(u1.z, u1.w));
      }
      if (c.wg == 0 && c.tid == 0) TS2(61);
      __threadfence();
      __syncwarp();
      if (c.wg == 0 && c.tid == 0) TS2(62);
      if (lane < 4 && lane != p) flag_add(pf + lane);
      if (lane == 0) flag_wait(pf + p, 24, 6);
      __syncwarp();
      if (c.wg == 0 && c.tid == 0) TS(9);
      const int nit = nch >> 3;
      uint4 v[5][4];
#pragma unroll
      for (int i = 0; i < 5; ++i) {
        if (i < nit) {
          const int e = t256 + i * 256;
          const int rl = e / nch, cI = e - rl * nch, r = 32 * p + rl;
#pragma unroll
          for (int k = 0; k < 3; ++k) v[i][k] = __ldcg(xs + ((size_t)(k + (k >= p)) * 128 + r) * 40 + cI);
          v[i][3] = __ldg((const uint4*)(x + (size_t)(row0 + r) * D_ + ncol0 + cI * 8));
        }
      }
#pragma unroll
      for (int i = 0; i < 5; ++i) {
        if (i < nit) {
          const int e = t256 + i * 256;
          const int rl = e / nch, cI = e - rl * nch, r = 32 * p + rl;
          const float4 u0 = *(const float4*)(sgen + r * pitch + cI * 32), u1 = *(const float4*)(sgen + r * pitch + cI * 32 + 16);
          float f[8] = {u0.x, u0.y, u0.z, u0.w, u1.x, u1.y, u1.z, u1.w};
          uint32_t o[4];
#pragma unroll
          for (int e2 = 0; e2 < 4; ++e2) {
            const uint32_t w0 = ((const uint32_t*)&v[i][0])[e2], w1 = ((const uint32_t*)&v[i][1])[e2], w2 = ((const uint32_t*)&v[i][2])[e2], w3 = ((const uint32_t*)&v[i][3])[e2];
            float lo = f[2 * e2] + ((__uint_as_float(w0 << 16) + __uint_as_float(w1 << 16)) + (__uint_as_float(w2 << 16) + __uint_as_float(w3 << 16)));
            float hi = f[2 * e2 + 1] + ((__uint_as_float(w0 & 0xffff0000u) + __uint_as_float(w1 & 0xffff0000u)) + (__uint_as_float(w2 & 0xffff0000u) + __uint_as_float(w3 & 0xffff0000u)));
            o[e2] = pack_bf16(lo, hi);
          }
          *(uint4*)(out + (size_t)(row0 + r) * D_ + ncol0 + cI * 8) = make_uint4(o[0], o[1], o[2], o[3]);
        }
      }
      if (c.wg == 0 && c.tid == 0) TS(10);
    }
    named_bar(1 + c.wg, 128);
    if (c.tid == 0) agent_exit();
  }
}

typedef CUresult (*EncodeFn)(CUtensorMap*, CUtensorMapDataType, cuuint32_t, void*, const cuuint64_t*, const cuuint64_t*,
                             const cuuint32_t*, const cuuint32_t*, CUtensorMapInterleave, CUtensorMapSwizzle,
                             CUtensorMapL2promotion, CUtensorMapFloatOOBfill);

static void make_map2(EncodeFn enc, CUtensorMap* mp, const void* ptr, int rows, int cols, int box_rows) {
  cuuint64_t dims[2] = {(cuuint64_t)cols, (cuuint64_t)rows};
  cuuint64_t strides[1] = {(cuuint64_t)cols * 2};
  cuuint32_t box[2] = {64, (cuuint32_t)box_rows};
  cuuint32_t es[2] = {1, 1};
  enc(mp, CU_TENSOR_MAP_DATA_TYPE_BFLOAT16, 2, (void*)ptr, dims, strides, box, es, CU_TENSOR_MAP_INTERLEAVE_NONE,
      CU_TENSOR_MAP_SWIZZLE_128B, CU_TENSOR_MAP_L2_PROMOTION_L2_256B, CU_TENSOR_MAP_FLOAT_OOB_FILL_NONE);
}
static void make_map3(EncodeFn enc, CUtensorMap* mp, const void* ptr, int rows, int cols, int nblk) {
  cuuint64_t dims[3] = {64, (cuuint64_t)rows, (cuuint64_t)(cols / 64)};
  cuuint64_t strides[2] = {(cuuint64_t)cols * 2, 128};
  cuuint32_t box[3] = {64, 32, (cuuint32_t)nblk};
  cuuint32_t es[3] = {1, 1, 1};
  enc(mp, CU_TENSOR_MAP_DATA_TYPE_BFLOAT16, 3, (void*)ptr, dims, strides, box, es, CU_TENSOR_MAP_INTERLEAVE_NONE,
      CU_TENSOR_MAP_SWIZZLE_128B, CU_TENSOR_MAP_L2_PROMOTION_L2_256B, CU_TENSOR_MAP_FLOAT_OOB_FILL_NONE);
}

extern "C" void kernel_launch(void* const* d_in, const int* in_sizes, int n_in, void* d_out, int out_size) {
  static EncodeFn enc = nullptr;
  static void* act_ptr = nullptr;
  if (!enc) {
    void* fn = nullptr;
    cudaDriverEntryPointQueryResult qr;
    cudaGetDriverEntryPoint("cuTensorMapEncodeTiled", &fn, cudaEnableDefault, &qr);
    enc = (EncodeFn)fn;
    cudaGetSymbolAddress(&act_ptr, g_act);
    cudaFuncSetAttribute(fused_kernel, cudaFuncAttributeMaxDynamicSharedMemorySize, SMEM_BYTES);
  }
  const __nv_bfloat16* x = (const __nv_bfloat16*)d_in[0];
  CUtensorMap m_qkv1, m_qkv2, m_gate2, m_up2, m_wo5, m_wo4, m_down5, m_down4, m_act;
  make_map3(enc, &m_qkv1, d_in[1], D_, QKV_, 1);
  make_map3(enc, &m_qkv2, d_in[1], D_, QKV_, 2);
  make_map3(enc, &m_gate2, d_in[4], D_, F_, 2);
  make_map3(enc, &m_up2, d_in[5], D_, F_, 2);
  make_map3(enc, &m_wo5, d_in[2], D_, D_, 5);
  make_map3(enc, &m_wo4, d_in[2], D_, D_, 4);
  make_map3(enc, &m_down5, d_in[6], F_, D_, 5);
  make_map3(enc, &m_down4, d_in[6], F_, D_, 4);
  make_map2(enc, &m_act, act_ptr, S_, ACT_, 128);
  fused_kernel<<<128, 384, SMEM_BYTES>>>(m_qkv1, m_qkv2, m_gate2, m_up2, m_wo5, m_wo4, m_down5, m_down4, m_act, x, (__nv_bfloat16*)d_out);
}
```

```cpp
#include <cuda_runtime.h>
#include <cuda_bf16.h>
#include <cuda.h>
#include <stdint.h>

constexpr int S_ = 2048, D_ = 576, F_ = 4608, QKV_ = 1728, ACT_ = 5184;
constexpr int NS1 = 7;
constexpr int NS2 = 4;
constexpr int XN_BYTES = 9 * 16384;
constexpr int RING1_OFF = 7 * 16384;
__device__ __forceinline__ uint32_t slot1_off(uint32_t s) { return RING1_OFF + (s >= 5 ? s - 5 : s + 2) * 16384; }
constexpr int ST1_BYTES = 16384;
constexpr int ST2_BYTES = 57344;
constexpr int DATA_BYTES = 229376;
constexpr int SMEM_BYTES = DATA_BYTES + 1024 + 512;
constexpr int NAGENTS = 128 * 4;
#define SKEW 0
#define MC 1

__device__ __align__(1024) __nv_bfloat16 g_qkv[S_ * QKV_];
__device__ __align__(1024) __nv_bfloat16 g_act[S_ * ACT_];
__device__ __align__(1024) uint4 g_xch[16 * 2 * 4 * 128 * 40];
__device__ unsigned int g_flags[288];
#define TS(i)
#define TS2(i)
#define FAIL(code) __trap()
#define SPIN_MAX (1u << 24)

__device__ __forceinline__ void wgmma_n128(float (&d)[64], uint64_t da, uint64_t db, int scale_d) {
  asm volatile("{\n.reg .pred p;\nsetp.ne.b32 p, %66, 0;\n"
    "wgmma.mma_async.sync.aligned.m64n128k16.f32.bf16.bf16 {%0, %1, %2, %3, %4, %5, %6, %7, %8, %9, %10, %11, %12, %13, %14, %15, %16, %17, %18, %19, %20, %21, %22, %23, %24, %25, %26, %27, %28, %29, %30, %31, %32, %33, %34, %35, %36, %37, %38, %39, %40, %41, %42, %43, %44, %45, %46, %47, %48, %49, %50, %51, %52, %53, %54, %55, %56, %57, %58, %59, %60, %61, %62, %63}, %64, %65, p, 1, 1, 0, 1;\n}\n"
    : "+f"(d[0]), "+f"(d[1]), "+f"(d[2]), "+f"(d[3]), "+f"(d[4]), "+f"(d[5]), "+f"(d[6]), "+f"(d[7]), "+f"(d[8]), "+f"(d[9]), "+f"(d[10]), "+f"(d[11]), "+f"(d[12]), "+f"(d[13]), "+f"(d[14]), "+f"(d[15]), "+f"(d[16]), "+f"(d[17]), "+f"(d[18]), "+f"(d[19]), "+f"(d[20]), "+f"(d[21]), "+f"(d[22]), "+f"(d[23]), "+f"(d[24]), "+f"(d[25]), "+f"(d[26]), "+f"(d[27]), "+f"(d[28]), "+f"(d[29]), "+f"(d[30]), "+f"(d[31]), "+f"(d[32]), "+f"(d[33]), "+f"(d[34]), "+f"(d[35]), "+f"(d[36]), "+f"(d[37]), "+f"(d[38]), "+f"(d[39]), "+f"(d[40]), "+f"(d[41]), "+f"(d[42]), "+f"(d[43]), "+f"(d[44]), "+f"(d[45]), "+f"(d[46]), "+f"(d[47]), "+f"(d[48]), "+f"(d[49]), "+f"(d[50]), "+f"(d[51]), "+f"(d[52]), "+f"(d[53]), "+f"(d[54]), "+f"(d[55]), "+f"(d[56]), "+f"(d[57]), "+f"(d[58]), "+f"(d[59]), "+f"(d[60]), "+f"(d[61]), "+f"(d[62]), "+f"(d[63])
    : "l"(da), "l"(db), "r"(scale_d));
}

__device__ __forceinline__ void wgmma_n192(float (&d)[96], uint64_t da, uint64_t db, int scale_d) {
  asm volatile("{\n.reg .pred p;\nsetp.ne.b32 p, %98, 0;\n"
    "wgmma.mma_async.sync.aligned.m64n192k16.f32.bf16.bf16 {%0, %1, %2, %3, %4, %5, %6, %7, %8, %9, %10, %11, %12, %13, %14, %15, %16, %17, %18, %19, %20, %21, %22, %23, %24, %25, %26, %27, %28, %29, %30, %31, %32, %33, %34, %35, %36, %37, %38, %39, %40, %41, %42, %43, %44, %45, %46, %47, %48, %49, %50, %51, %52, %53, %54, %55, %56, %57, %58, %59, %60, %61, %62, %63, %64, %65, %66, %67, %68, %69, %70, %71, %72, %73, %74, %75, %76, %77, %78, %79, %80, %81, %82, %83, %84, %85, %86, %87, %88, %89, %90, %91, %92, %93, %94, %95}, %96, %97, p, 1, 1, 0, 1;\n}\n"
    : "+f"(d[0]), "+f"(d[1]), "+f"(d[2]), "+f"(d[3]), "+f"(d[4]), "+f"(d[5]), "+f"(d[6]), "+f"(d[7]), "+f"(d[8]), "+f"(d[9]), "+f"(d[10]), "+f"(d[11]), "+f"(d[12]), "+f"(d[13]), "+f"(d[14]), "+f"(d[15]), "+f"(d[16]), "+f"(d[17]), "+f"(d[18]), "+f"(d[19]), "+f"(d[20]), "+f"(d[21]), "+f"(d[22]), "+f"(d[23]), "+f"(d[24]), "+f"(d[25]), "+f"(d[26]), "+f"(d[27]), "+f"(d[28]), "+f"(d[29]), "+f"(d[30]), "+f"(d[31]), "+f"(d[32]), "+f"(d[33]), "+f"(d[34]), "+f"(d[35]), "+f"(d[36]), "+f"(d[37]), "+f"(d[38]), "+f"(d[39]), "+f"(d[40]), "+f"(d[41]), "+f"(d[42]), "+f"(d[43]), "+f"(d[44]), "+f"(d[45]), "+f"(d[46]), "+f"(d[47]), "+f"(d[48]), "+f"(d[49]), "+f"(d[50]), "+f"(d[51]), "+f"(d[52]), "+f"(d[53]), "+f"(d[54]), "+f"(d[55]), "+f"(d[56]), "+f"(d[57]), "+f"(d[58]), "+f"(d[59]), "+f"(d[60]), "+f"(d[61]), "+f"(d[62]), "+f"(d[63]), "+f"(d[64]), "+f"(d[65]), "+f"(d[66]), "+f"(d[67]), "+f"(d[68]), "+f"(d[69]), "+f"(d[70]), "+f"(d[71]), "+f"(d[72]), "+f"(d[73]), "+f"(d[74]), "+f"(d[75]), "+f"(d[76]), "+f"(d[77]), "+f"(d[78]), "+f"(d[79]), "+f"(d[80]), "+f"(d[81]), "+f"(d[82]), "+f"(d[83]), "+f"(d[84]), "+f"(d[85]), "+f"(d[86]), "+f"(d[87]), "+f"(d[88]), "+f"(d[89]), "+f"(d[90]), "+f"(d[91]), "+f"(d[92]), "+f"(d[93]), "+f"(d[94]), "+f"(d[95])
    : "l"(da), "l"(db), "r"(scale_d));
}

__device__ __forceinline__ void wgmma_n256(float (&d)[128], uint64_t da, uint64_t db, int scale_d) {
  asm volatile("{\n.reg .pred p;\nsetp.ne.b32 p, %130, 0;\n"
    "wgmma.mma_async.sync.aligned.m64n256k16.f32.bf16.bf16 {%0, %1, %2, %3, %4, %5, %6, %7, %8, %9, %10, %11, %12, %13, %14, %15, %16, %17, %18, %19, %20, %21, %22, %23, %24, %25, %26, %27, %28, %29, %30, %31, %32, %33, %34, %35, %36, %37, %38, %39, %40, %41, %42, %43, %44, %45, %46, %47, %48, %49, %50, %51, %52, %53, %54, %55, %56, %57, %58, %59, %60, %61, %62, %63, %64, %65, %66, %67, %68, %69, %70, %71, %72, %73, %74, %75, %76, %77, %78, %79, %80, %81, %82, %83, %84, %85, %86, %87, %88, %89, %90, %91, %92, %93, %94, %95, %96, %97, %98, %99, %100, %101, %102, %103, %104, %105, %106, %107, %108, %109, %110, %111, %112, %113, %114, %115, %116, %117, %118, %119, %120, %121, %122, %123, %124, %125, %126, %127}, %128, %129, p, 1, 1, 0, 1;\n}\n"
    : "+f"(d[0]), "+f"(d[1]), "+f"(d[2]), "+f"(d[3]), "+f"(d[4]), "+f"(d[5]), "+f"(d[6]), "+f"(d[7]), "+f"(d[8]), "+f"(d[9]), "+f"(d[10]), "+f"(d[11]), "+f"(d[12]), "+f"(d[13]), "+f"(d[14]), "+f"(d[15]), "+f"(d[16]), "+f"(d[17]), "+f"(d[18]), "+f"(d[19]), "+f"(d[20]), "+f"(d[21]), "+f"(d[22]), "+f"(d[23]), "+f"(d[24]), "+f"(d[25]), "+f"(d[26]), "+f"(d[27]), "+f"(d[28]), "+f"(d[29]), "+f"(d[30]), "+f"(d[31]), "+f"(d[32]), "+f"(d[33]), "+f"(d[34]), "+f"(d[35]), "+f"(d[36]), "+f"(d[37]), "+f"(d[38]), "+f"(d[39]), "+f"(d[40]), "+f"(d[41]), "+f"(d[42]), "+f"(d[43]), "+f"(d[44]), "+f"(d[45]), "+f"(d[46]), "+f"(d[47]), "+f"(d[48]), "+f"(d[49]), "+f"(d[50]), "+f"(d[51]), "+f"(d[52]), "+f"(d[53]), "+f"(d[54]), "+f"(d[55]), "+f"(d[56]), "+f"(d[57]), "+f"(d[58]), "+f"(d[59]), "+f"(d[60]), "+f"(d[61]), "+f"(d[62]), "+f"(d[63]), "+f"(d[64]), "+f"(d[65]), "+f"(d[66]), "+f"(d[67]), "+f"(d[68]), "+f"(d[69]), "+f"(d[70]), "+f"(d[71]), "+f"(d[72]), "+f"(d[73]), "+f"(d[74]), "+f"(d[75]), "+f"(d[76]), "+f"(d[77]), "+f"(d[78]), "+f"(d[79]), "+f"(d[80]), "+f"(d[81]), "+f"(d[82]), "+f"(d[83]), "+f"(d[84]), "+f"(d[85]), "+f"(d[86]), "+f"(d[87]), "+f"(d[88]), "+f"(d[89]), "+f"(d[90]), "+f"(d[91]), "+f"(d[92]), "+f"(d[93]), "+f"(d[94]), "+f"(d[95]), "+f"(d[96]), "+f"(d[97]), "+f"(d[98]), "+f"(d[99]), "+f"(d[100]), "+f"(d[101]), "+f"(d[102]), "+f"(d[103]), "+f"(d[104]), "+f"(d[105]), "+f"(d[106]), "+f"(d[107]), "+f"(d[108]), "+f"(d[109]), "+f"(d[110]), "+f"(d[111]), "+f"(d[112]), "+f"(d[113]), "+f"(d[114]), "+f"(d[115]), "+f"(d[116]), "+f"(d[117]), "+f"(d[118]), "+f"(d[119]), "+f"(d[120]), "+f"(d[121]), "+f"(d[122]), "+f"(d[123]), "+f"(d[124]), "+f"(d[125]), "+f"(d[126]), "+f"(d[127])
    : "l"(da), "l"(db), "r"(scale_d));
}

__device__ __forceinline__ void wgmma_rs_n128(float (&d)[64], const uint32_t (&a)[4], uint64_t db) {
  asm volatile(
    "wgmma.mma_async.sync.aligned.m64n128k16.f32.bf16.bf16 {%0, %1, %2, %3, %4, %5, %6, %7, %8, %9, %10, %11, %12, %13, %14, %15, %16, %17, %18, %19, %20, %21, %22, %23, %24, %25, %26, %27, %28, %29, %30, %31, %32, %33, %34, %35, %36, %37, %38, %39, %40, %41, %42, %43, %44, %45, %46, %47, %48, %49, %50, %51, %52, %53, %54, %55, %56, %57, %58, %59, %60, %61, %62, %63}, {%64, %65, %66, %67}, %68, 1, 1, 1, 1;\n"
    : "+f"(d[0]), "+f"(d[1]), "+f"(d[2]), "+f"(d[3]), "+f"(d[4]), "+f"(d[5]), "+f"(d[6]), "+f"(d[7]), "+f"(d[8]), "+f"(d[9]), "+f"(d[10]), "+f"(d[11]), "+f"(d[12]), "+f"(d[13]), "+f"(d[14]), "+f"(d[15]), "+f"(d[16]), "+f"(d[17]), "+f"(d[18]), "+f"(d[19]), "+f"(d[20]), "+f"(d[21]), "+f"(d[22]), "+f"(d[23]), "+f"(d[24]), "+f"(d[25]), "+f"(d[26]), "+f"(d[27]), "+f"(d[28]), "+f"(d[29]), "+f"(d[30]), "+f"(d[31]), "+f"(d[32]), "+f"(d[33]), "+f"(d[34]), "+f"(d[35]), "+f"(d[36]), "+f"(d[37]), "+f"(d[38]), "+f"(d[39]), "+f"(d[40]), "+f"(d[41]), "+f"(d[42]), "+f"(d[43]), "+f"(d[44]), "+f"(d[45]), "+f"(d[46]), "+f"(d[47]), "+f"(d[48]), "+f"(d[49]), "+f"(d[50]), "+f"(d[51]), "+f"(d[52]), "+f"(d[53]), "+f"(d[54]), "+f"(d[55]), "+f"(d[56]), "+f"(d[57]), "+f"(d[58]), "+f"(d[59]), "+f"(d[60]), "+f"(d[61]), "+f"(d[62]), "+f"(d[63])
    : "r"(a[0]), "r"(a[1]), "r"(a[2]), "r"(a[3]), "l"(db));
}

__device__ __forceinline__ void wgmma_rs_n192(float (&d)[96], const uint32_t (&a)[4], uint64_t db) {
  asm volatile(
    "wgmma.mma_async.sync.aligned.m64n192k16.f32.bf16.bf16 {%0, %1, %2, %3, %4, %5, %6, %7, %8, %9, %10, %11, %12, %13, %14, %15, %16, %17, %18, %19, %20, %21, %22, %23, %24, %25, %26, %27, %28, %29, %30, %31, %32, %33, %34, %35, %36, %37, %38, %39, %40, %41, %42, %43, %44, %45, %46, %47, %48, %49, %50, %51, %52, %53, %54, %55, %56, %57, %58, %59, %60, %61, %62, %63, %64, %65, %66, %67, %68, %69, %70, %71, %72, %73, %74, %75, %76, %77, %78, %79, %80, %81, %82, %83, %84, %85, %86, %87, %88, %89, %90, %91, %92, %93, %94, %95}, {%96, %97, %98, %99}, %100, 1, 1, 1, 1;\n"
    : "+f"(d[0]), "+f"(d[1]), "+f"(d[2]), "+f"(d[3]), "+f"(d[4]), "+f"(d[5]), "+f"(d[6]), "+f"(d[7]), "+f"(d[8]), "+f"(d[9]), "+f"(d[10]), "+f"(d[11]), "+f"(d[12]), "+f"(d[13]), "+f"(d[14]), "+f"(d[15]), "+f"(d[16]), "+f"(d[17]), "+f"(d[18]), "+f"(d[19]), "+f"(d[20]), "+f"(d[21]), "+f"(d[22]), "+f"(d[23]), "+f"(d[24]), "+f"(d[25]), "+f"(d[26]), "+f"(d[27]), "+f"(d[28]), "+f"(d[29]), "+f"(d[30]), "+f"(d[31]), "+f"(d[32]), "+f"(d[33]), "+f"(d[34]), "+f"(d[35]), "+f"(d[36]), "+f"(d[37]), "+f"(d[38]), "+f"(d[39]), "+f"(d[40]), "+f"(d[41]), "+f"(d[42]), "+f"(d[43]), "+f"(d[44]), "+f"(d[45]), "+f"(d[46]), "+f"(d[47]), "+f"(d[48]), "+f"(d[49]), "+f"(d[50]), "+f"(d[51]), "+f"(d[52]), "+f"(d[53]), "+f"(d[54]), "+f"(d[55]), "+f"(d[56]), "+f"(d[57]), "+f"(d[58]), "+f"(d[59]), "+f"(d[60]), "+f"(d[61]), "+f"(d[62]), "+f"(d[63]), "+f"(d[64]), "+f"(d[65]), "+f"(d[66]), "+f"(d[67]), "+f"(d[68]), "+f"(d[69]), "+f"(d[70]), "+f"(d[71]), "+f"(d[72]), "+f"(d[73]), "+f"(d[74]), "+f"(d[75]), "+f"(d[76]), "+f"(d[77]), "+f"(d[78]), "+f"(d[79]), "+f"(d[80]), "+f"(d[81]), "+f"(d[82]), "+f"(d[83]), "+f"(d[84]), "+f"(d[85]), "+f"(d[86]), "+f"(d[87]), "+f"(d[88]), "+f"(d[89]), "+f"(d[90]), "+f"(d[91]), "+f"(d[92]), "+f"(d[93]), "+f"(d[94]), "+f"(d[95])
    : "r"(a[0]), "r"(a[1]), "r"(a[2]), "r"(a[3]), "l"(db));
}

__device__ __forceinline__ void wgmma_rs_n256(float (&d)[128], const uint32_t (&a)[4], uint64_t db) {
  asm volatile(
    "wgmma.mma_async.sync.aligned.m64n256k16.f32.bf16.bf16 {%0, %1, %2, %3, %4, %5, %6, %7, %8, %9, %10, %11, %12, %13, %14, %15, %16, %17, %18, %19, %20, %21, %22, %23, %24, %25, %26, %27, %28, %29, %30, %31, %32, %33, %34, %35, %36, %37, %38, %39, %40, %41, %42, %43, %44, %45, %46, %47, %48, %49, %50, %51, %52, %53, %54, %55, %56, %57, %58, %59, %60, %61, %62, %63, %64, %65, %66, %67, %68, %69, %70, %71, %72, %73, %74, %75, %76, %77, %78, %79, %80, %81, %82, %83, %84, %85, %86, %87, %88, %89, %90, %91, %92, %93, %94, %95, %96, %97, %98, %99, %100, %101, %102, %103, %104, %105, %106, %107, %108, %109, %110, %111, %112, %113, %114, %115, %116, %117, %118, %119, %120, %121, %122, %123, %124, %125, %126, %127}, {%128, %129, %130, %131}, %132, 1, 1, 1, 1;\n"
    : "+f"(d[0]), "+f"(d[1]), "+f"(d[2]), "+f"(d[3]), "+f"(d[4]), "+f"(d[5]), "+f"(d[6]), "+f"(d[7]), "+f"(d[8]), "+f"(d[9]), "+f"(d[10]), "+f"(d[11]), "+f"(d[12]), "+f"(d[13]), "+f"(d[14]), "+f"(d[15]), "+f"(d[16]), "+f"(d[17]), "+f"(d[18]), "+f"(d[19]), "+f"(d[20]), "+f"(d[21]), "+f"(d[22]), "+f"(d[23]), "+f"(d[24]), "+f"(d[25]), "+f"(d[26]), "+f"(d[27]), "+f"(d[28]), "+f"(d[29]), "+f"(d[30]), "+f"(d[31]), "+f"(d[32]), "+f"(d[33]), "+f"(d[34]), "+f"(d[35]), "+f"(d[36]), "+f"(d[37]), "+f"(d[38]), "+f"(d[39]), "+f"(d[40]), "+f"(d[41]), "+f"(d[42]), "+f"(d[43]), "+f"(d[44]), "+f"(d[45]), "+f"(d[46]), "+f"(d[47]), "+f"(d[48]), "+f"(d[49]), "+f"(d[50]), "+f"(d[51]), "+f"(d[52]), "+f"(d[53]), "+f"(d[54]), "+f"(d[55]), "+f"(d[56]), "+f"(d[57]), "+f"(d[58]), "+f"(d[59]), "+f"(d[60]), "+f"(d[61]), "+f"(d[62]), "+f"(d[63]), "+f"(d[64]), "+f"(d[65]), "+f"(d[66]), "+f"(d[67]), "+f"(d[68]), "+f"(d[69]), "+f"(d[70]), "+f"(d[71]), "+f"(d[72]), "+f"(d[73]), "+f"(d[74]), "+f"(d[75]), "+f"(d[76]), "+f"(d[77]), "+f"(d[78]), "+f"(d[79]), "+f"(d[80]), "+f"(d[81]), "+f"(d[82]), "+f"(d[83]), "+f"(d[84]), "+f"(d[85]), "+f"(d[86]), "+f"(d[87]), "+f"(d[88]), "+f"(d[89]), "+f"(d[90]), "+f"(d[91]), "+f"(d[92]), "+f"(d[93]), "+f"(d[94]), "+f"(d[95]), "+f"(d[96]), "+f"(d[97]), "+f"(d[98]), "+f"(d[99]), "+f"(d[100]), "+f"(d[101]), "+f"(d[102]), "+f"(d[103]), "+f"(d[104]), "+f"(d[105]), "+f"(d[106]), "+f"(d[107]), "+f"(d[108]), "+f"(d[109]), "+f"(d[110]), "+f"(d[111]), "+f"(d[112]), "+f"(d[113]), "+f"(d[114]), "+f"(d[115]), "+f"(d[116]), "+f"(d[117]), "+f"(d[118]), "+f"(d[119]), "+f"(d[120]), "+f"(d[121]), "+f"(d[122]), "+f"(d[123]), "+f"(d[124]), "+f"(d[125]), "+f"(d[126]), "+f"(d[127])
    : "r"(a[0]), "r"(a[1]), "r"(a[2]), "r"(a[3]), "l"(db));
}

__device__ __forceinline__ uint32_t smem_u32(const void* p) { return (uint32_t)__cvta_generic_to_shared(p); }
__device__ __forceinline__ void mbar_init(uint32_t a, uint32_t cnt) { asm volatile("mbarrier.init.shared::cta.b64 [%0], %1;" ::"r"(a), "r"(cnt)); }
__device__ __forceinline__ void mbar_expect_tx(uint32_t a, uint32_t bytes) {
  asm volatile("mbarrier.arrive.expect_tx.shared::cta.b64 _, [%0], %1;" ::"r"(a), "r"(bytes) : "memory");
}
__device__ __forceinline__ void mbar_arrive_cluster(uint32_t a, uint32_t cta) {
  asm volatile("{\n.reg .b32 ra;\nmapa.shared::cluster.u32 ra, %0, %1;\nmbarrier.arrive.shared::cluster.b64 _, [ra];\n}\n" ::"r"(a), "r"(cta) : "memory");
}
__device__ __forceinline__ void mbar_arrive_both(uint32_t a) {
  mbar_arrive_cluster(a, 0); mbar_arrive_cluster(a, 1);
}
__device__ __forceinline__ void mbar_wait(uint32_t a, uint32_t parity, int code) {
  uint32_t ok = 0;
#pragma unroll 1
  for (uint32_t it = 0; it < SPIN_MAX; ++it) {
    asm volatile("{\n.reg .pred p;\nmbarrier.try_wait.parity.shared::cta.b64 p, [%1], %2;\nselp.u32 %0, 1, 0, p;\n}\n" : "=r"(ok) : "r"(a), "r"(parity) : "memory");
    if (ok) return;
  }
  FAIL(code);
}
__device__ __forceinline__ bool mbar_test(uint32_t a, uint32_t parity) {
  uint32_t ok;
  asm volatile("{\n.reg .pred p;\nmbarrier.test_wait.parity.shared::cta.b64 p, [%1], %2;\nselp.u32 %0, 1, 0, p;\n}\n" : "=r"(ok) : "r"(a), "r"(parity) : "memory");
  return __all_sync(0xffffffffu, ok != 0);
}
__device__ __forceinline__ void tma_load_2d(uint32_t dst, const CUtensorMap* map, int c0, int c1, uint32_t mbar) {
  asm volatile("cp.async.bulk.tensor.2d.shared::cluster.global.mbarrier::complete_tx::bytes [%0], [%1, {%3, %4}], [%2];" ::"r"(dst), "l"(map), "r"(mbar), "r"(c0), "r"(c1) : "memory");
}
__device__ __forceinline__ void tma_load_2d_mc(uint32_t dst, const CUtensorMap* map, int c0, int c1, uint32_t mbar, uint16_t mask) {
  asm volatile("cp.async.bulk.tensor.2d.shared::cluster.global.mbarrier::complete_tx::bytes.multicast::cluster [%0], [%1, {%3, %4}], [%2], %5;" ::"r"(dst), "l"(map), "r"(mbar), "r"(c0), "r"(c1), "h"(mask) : "memory");
}
__device__ __forceinline__ void tma_load_3d_mc(uint32_t dst, const CUtensorMap* map, int c0, int c1, int c2, uint32_t mbar, uint16_t mask) {
  asm volatile("cp.async.bulk.tensor.3d.shared::cluster.global.mbarrier::complete_tx::bytes.multicast::cluster [%0], [%1, {%3, %4, %5}], [%2], %6;" ::"r"(dst), "l"(map), "r"(mbar), "r"(c0), "r"(c1), "r"(c2), "h"(mask) : "memory");
}
__device__ __forceinline__ void tma_prefetch_3d(const CUtensorMap* map, int c0, int c1, int c2) {
  asm volatile("cp.async.bulk.prefetch.tensor.3d.L2.global.tile [%0, {%1, %2, %3}];" ::"l"(map), "r"(c0), "r"(c1), "r"(c2) : "memory");
}
__device__ __forceinline__ void wgmma_fence() { asm volatile("wgmma.fence.sync.aligned;" ::: "memory"); }
__device__ __forceinline__ void wgmma_commit() { asm volatile("wgmma.commit_group.sync.aligned;" ::: "memory"); }
template <int N> __device__ __forceinline__ void wgmma_wait() { asm volatile("wgmma.wait_group.sync.aligned %0;" ::"n"(N) : "memory"); }
__device__ __forceinline__ uint64_t make_desc(uint32_t saddr, uint32_t lbo, uint32_t sbo) {
  return (uint64_t)((saddr & 0x3FFFF) >> 4) | ((uint64_t)(lbo >> 4) << 16) | ((uint64_t)(sbo >> 4) << 32) | (1ull << 62);
}
__device__ __forceinline__ void fence_proxy_async() { asm volatile("fence.proxy.async.global;" ::: "memory"); }
__device__ __forceinline__ void named_bar(int id, int n) { asm volatile("bar.sync %0, %1;" ::"r"(id), "r"(n) : "memory"); }
__device__ __forceinline__ void cluster_sync() {
  asm volatile("barrier.cluster.arrive.release.aligned;\nbarrier.cluster.wait.acquire.aligned;" ::: "memory");
}
__device__ __forceinline__ unsigned ld_acquire(const unsigned* p) {
  unsigned v;
  asm volatile("ld.acquire.gpu.global.u32 %0, [%1];" : "=r"(v) : "l"(p) : "memory");
  return v;
}
__device__ __forceinline__ unsigned flag_wait(const unsigned* p, unsigned target, int code) {
#pragma unroll 1
  for (uint32_t it = 0; it < SPIN_MAX; ++it) {
    unsigned v = ld_acquire(p);
    if (v >= target) return v;
    __nanosleep(20);
  }
  FAIL(code);
  return 0;
}
__device__ __forceinline__ void flag_add(unsigned* p) {
  asm volatile("red.release.gpu.global.add.u32 [%0], 1;" ::"l"(p) : "memory");
}
__device__ __forceinline__ void agent_exit() {
  __threadfence();
  unsigned old = atomicAdd(&g_flags[272], 1u);
  if (old == NAGENTS - 1) {
    for (int i = 0; i < 273; ++i) g_flags[i] = 0;
    __threadfence();
  }
}
__device__ __forceinline__ float bf16r(float v) { return __bfloat162float(__float2bfloat16_rn(v)); }
__device__ __forceinline__ uint32_t pack_bf16(float lo, float hi) {
  uint32_t r;
  asm("cvt.rn.bf16x2.f32 %0, %1, %2;" : "=r"(r) : "f"(hi), "f"(lo));
  return r;
}
__device__ __forceinline__ void quad_transpose(uint32_t& v0, uint32_t& v1, uint32_t& v2, uint32_t& v3, int q) {
  bool b0 = q & 1;
  uint32_t s0 = b0 ? v0 : v1, s1 = b0 ? v2 : v3;
  s0 = __shfl_xor_sync(0xffffffffu, s0, 1);
  s1 = __shfl_xor_sync(0xffffffffu, s1, 1);
  if (b0) { v0 = s0; v2 = s1; } else { v1 = s0; v3 = s1; }
  bool b1 = q & 2;
  s0 = b1 ? v0 : v2; s1 = b1 ? v1 : v3;
  s0 = __shfl_xor_sync(0xffffffffu, s0, 2);
  s1 = __shfl_xor_sync(0xffffffffu, s1, 2);
  if (b1) { v0 = s0; v1 = s1; } else { v2 = s0; v3 = s1; }
}

struct Tile { int is_h; int col; int nb; };
__device__ __forceinline__ int num_tiles(int j) { return j ? 6 : 5; }
__device__ __forceinline__ Tile get_tile(int p, int j, int t) {
  Tile T;
  if (t == 0) {
    T.is_h = 0;
    if (j == 0) { T.col = 256 * p; T.nb = 4; }
    else { T.col = 1024 + 192 * p; T.nb = (p == 3) ? 2 : 3; }
  } else {
    T.is_h = 1; T.col = 128 * (9 * p + (j ? 4 : 0) + (t - 1)); T.nb = 4;
  }
  return T;
}

template <int NB> struct Acc { float a[NB * 32]; };
template <int NB> __device__ __forceinline__ void wgmma_nb(float (&d)[NB * 32], uint64_t da, uint64_t db, int sc);
template <> __device__ __forceinline__ void wgmma_nb<2>(float (&d)[64], uint64_t da, uint64_t db, int sc) { wgmma_n128(d, da, db, sc); }
template <> __device__ __forceinline__ void wgmma_nb<3>(float (&d)[96], uint64_t da, uint64_t db, int sc) { wgmma_n192(d, da, db, sc); }
template <> __device__ __forceinline__ void wgmma_nb<4>(float (&d)[128], uint64_t da, uint64_t db, int sc) { wgmma_n256(d, da, db, sc); }
template <int NB> __device__ __forceinline__ void wgmma_rs_nb(float (&d)[NB * 32], const uint32_t (&a)[4], uint64_t db);
template <> __device__ __forceinline__ void wgmma_rs_nb<2>(float (&d)[64], const uint32_t (&a)[4], uint64_t db) { wgmma_rs_n128(d, a, db); }
template <> __device__ __forceinline__ void wgmma_rs_nb<3>(float (&d)[96], const uint32_t (&a)[4], uint64_t db) { wgmma_rs_n192(d, a, db); }
template <> __device__ __forceinline__ void wgmma_rs_nb<4>(float (&d)[128], const uint32_t (&a)[4], uint64_t db) { wgmma_rs_n256(d, a, db); }

struct Ctx {
  uint32_t sbase;
  uint32_t full1, empty1, full2, empty2;
  uint32_t peer;
  int wg;
  int tid;
};

__device__ __forceinline__ void publish(unsigned* flag) {
  __threadfence();
  __syncwarp();
  if ((threadIdx.x & 31) == 0) flag_add(flag);
}
template <int NB>
__device__ __forceinline__ void g1_tile(const Ctx& c, float (&acc)[NB * 32], uint32_t& it  , const uint32_t (&areg)[8][4]) {
  const uint32_t abase = c.sbase + c.wg * 8192;
#pragma unroll 1
  for (int kb = 0; kb < 7; ++kb) {
    const uint32_t s0 = it % NS1, s1 = (it + 1) % NS1;
    const uint32_t a0 = abase + kb * 16384;
    const uint32_t b0 = c.sbase + slot1_off(s0), b1 = c.sbase + slot1_off(s1);
    mbar_wait(c.full1 + 8 * s0, (it / NS1) & 1, 0);
    mbar_wait(c.full1 + 8 * s1, ((it + 1) / NS1) & 1, 0);
    wgmma_fence();
    wgmma_nb<NB>(acc, make_desc(a0, 16, 1024), make_desc(b0, 4096, 1024), kb > 0);
    wgmma_nb<NB>(acc, make_desc(a0 + 32, 16, 1024), make_desc(b0 + 2048, 4096, 1024), 1);
    wgmma_nb<NB>(acc, make_desc(a0 + 64, 16, 1024), make_desc(b1, 4096, 1024), 1);
    wgmma_nb<NB>(acc, make_desc(a0 + 96, 16, 1024), make_desc(b1 + 2048, 4096, 1024), 1);
    wgmma_commit();
    wgmma_wait<1>();
    if (kb > 0 && c.tid == 0) { mbar_arrive_both(c.empty1 + 8 * ((it - 2) % NS1)); mbar_arrive_both(c.empty1 + 8 * ((it - 1) % NS1)); }
    it += 2;
  }
#pragma unroll
  for (int kk = 0; kk < 2; ++kk) {
    const uint32_t s0 = it % NS1, s1 = (it + 1) % NS1;
    const uint32_t b0 = c.sbase + slot1_off(s0), b1 = c.sbase + slot1_off(s1);
    mbar_wait(c.full1 + 8 * s0, (it / NS1) & 1, 0);
    mbar_wait(c.full1 + 8 * s1, ((it + 1) / NS1) & 1, 0);
    wgmma_fence();
    wgmma_rs_nb<NB>(acc, areg[4 * kk], make_desc(b0, 4096, 1024));
    wgmma_rs_nb<NB>(acc, areg[4 * kk + 1], make_desc(b0 + 2048, 4096, 1024));
    wgmma_rs_nb<NB>(acc, areg[4 * kk + 2], make_desc(b1, 4096, 1024));
    wgmma_rs_nb<NB>(acc, areg[4 * kk + 3], make_desc(b1 + 2048, 4096, 1024));
    wgmma_commit();
    wgmma_wait<1>();
    if (c.tid == 0) { mbar_arrive_both(c.empty1 + 8 * ((it - 2) % NS1)); mbar_arrive_both(c.empty1 + 8 * ((it - 1) % NS1)); }
    it += 2;
  }
  wgmma_wait<0>();
  if (c.tid == 0) { mbar_arrive_both(c.empty1 + 8 * ((it - 2) % NS1)); mbar_arrive_both(c.empty1 + 8 * ((it - 1) % NS1)); }
}

template <int NB>
__device__ __forceinline__ void epi_h(const Ctx& c, float (&acc)[NB * 32], int row0  , int hcol) {
  constexpr int G = NB * 4;
  const int lane = c.tid & 31, w = c.tid >> 5, q = lane & 3;
  const int r = row0 + c.wg * 64 + w * 16 + (lane >> 2);
  __nv_bfloat16* dst0 = g_act + (size_t)r * ACT_ + 576 + hcol + q * 8;
  __nv_bfloat16* dst1 = dst0 + 8 * ACT_;
  const __nv_bfloat162 zero2 = __floats2bfloat162_rn(0.f, 0.f);
#pragma unroll
  for (int a = 0; a < G / 4; ++a) {
    uint32_t v[4], u[4];
#pragma unroll
    for (int i = 0; i < 4; ++i) {
      int g = 4 * a + i;
      uint32_t g0 = pack_bf16(acc[4 * g], acc[4 * g + 1]), g1 = pack_bf16(acc[4 * g + 2], acc[4 * g + 3]);
      uint32_t u0 = pack_bf16(acc[4 * (g + G)], acc[4 * (g + G) + 1]), u1 = pack_bf16(acc[4 * (g + G) + 2], acc[4 * (g + G) + 3]);
      __nv_bfloat162 h0 = __hmul2(__hmax2(*(__nv_bfloat162*)&g0, zero2), *(__nv_bfloat162*)&u0);
      __nv_bfloat162 h1 = __hmul2(__hmax2(*(__nv_bfloat162*)&g1, zero2), *(__nv_bfloat162*)&u1);
      v[i] = *(uint32_t*)&h0; u[i] = *(uint32_t*)&h1;
    }
    quad_transpose(v[0], v[1], v[2], v[3], q);
    quad_transpose(u[0], u[1], u[2], u[3], q);
    *(uint4*)(dst0 + a * 32) = make_uint4(v[0], v[1], v[2], v[3]);
    *(uint4*)(dst1 + a * 32) = make_uint4(u[0], u[1], u[2], u[3]);
  }
}
template <int NB>
__device__ __forceinline__ void epi_qkv(const Ctx& c, float (&acc)[NB * 32], int row0, int col) {
  constexpr int G = NB * 8;
  const int lane = c.tid & 31, w = c.tid >> 5, q = lane & 3;
  const int r = row0 + c.wg * 64 + w * 16 + (lane >> 2);
  __nv_bfloat16* dst0 = g_qkv + (size_t)r * QKV_ + col + q * 8;
  __nv_bfloat16* dst1 = dst0 + 8 * QKV_;
#pragma unroll
  for (int a = 0; a < G / 4; ++a) {
    uint32_t v[4], u[4];
#pragma unroll
    for (int i = 0; i < 4; ++i) {
      int g = 4 * a + i;
      v[i] = pack_bf16(acc[4 * g], acc[4 * g + 1]); u[i] = pack_bf16(acc[4 * g + 2], acc[4 * g + 3]);
    }
    quad_transpose(v[0], v[1], v[2], v[3], q);
    quad_transpose(u[0], u[1], u[2], u[3], q);
    *(uint4*)(dst0 + a * 32) = make_uint4(v[0], v[1], v[2], v[3]);
    *(uint4*)(dst1 + a * 32) = make_uint4(u[0], u[1], u[2], u[3]);
  }
}
__device__ __forceinline__ void mbar_arrive_local(uint32_t a) { asm volatile("mbarrier.arrive.shared::cta.b64 _, [%0];" ::"r"(a) : "memory"); }

template <int NA>
__device__ __forceinline__ void acc_to_smem(float (&acc)[NA], uint32_t a0  , uint32_t pitch) {
#pragma unroll
  for (int g = 0; g < NA / 4; ++g) {
    asm volatile("st.shared.v2.f32 [%0], {%1, %2};" ::"r"(a0 + g * 32), "f"(acc[4 * g]), "f"(acc[4 * g + 1]) : "memory");
    asm volatile("st.shared.v2.f32 [%0], {%1, %2};" ::"r"(a0 + 8 * pitch + g * 32), "f"(acc[4 * g + 2]), "f"(acc[4 * g + 3]) : "memory");
  }
}
__device__ __forceinline__ float4 lds128(uint32_t a) {
  float4 v;
  asm volatile("ld.shared.v4.f32 {%0, %1, %2, %3}, [%4];" : "=f"(v.x), "=f"(v.y), "=f"(v.z), "=f"(v.w) : "r"(a) : "memory");
  return v;
}

__device__ __forceinline__ void mma16816(float (&c)[4], uint32_t a0, uint32_t a1, uint32_t a2, uint32_t a3, uint32_t b0, uint32_t b1) {
  asm volatile("mma.sync.aligned.m16n8k16.row.col.f32.bf16.bf16.f32 {%0,%1,%2,%3}, {%4,%5,%6,%7}, {%8,%9}, {%0,%1,%2,%3};"
               : "+f"(c[0]), "+f"(c[1]), "+f"(c[2]), "+f"(c[3]) : "r"(a0), "r"(a1), "r"(a2), "r"(a3), "r"(b0), "r"(b1));
}
__device__ __forceinline__ uint32_t movm(uint32_t a) {
  uint32_t d;
  asm volatile("movmatrix.sync.aligned.m8n8.trans.b16 %0, %1;" : "=r"(d) : "r"(a));
  return d;
}
struct HeadRegs { uint32_t q[2][3], k[4][3], v[4][3]; };
__device__ __forceinline__ void load_head(HeadRegs& R, int h, int qrow, int g, int t) {
  const int o = h & 1;
  const int wp = 9 * h + o + 2 * t, wt = 9 * h + (o ? 0 : 8);
#pragma unroll
  for (int r = 0; r < 2; ++r) {
    const uint32_t* p = (const uint32_t*)(g_qkv + (size_t)(qrow + g + 8 * r) * QKV_);
    uint2 a = *(const uint2*)(p + wp);
    R.q[r][0] = a.x; R.q[r][1] = a.y; R.q[r][2] = t == 0 ? p[wt] : 0u;
  }
#pragma unroll
  for (int nt = 0; nt < 4; ++nt) {
    const int jj = 8 * nt + g, kr = qrow - 14 + jj;
    const bool ok = (kr >= 0) && (jj < 30);
    const uint32_t* p = (const uint32_t*)(g_qkv + (size_t)(ok ? kr : qrow) * QKV_);
    uint2 a = make_uint2(0u, 0u);
    if (ok) a = *(const uint2*)(p + 288 + wp);
    R.k[nt][0] = a.x; R.k[nt][1] = a.y; R.k[nt][2] = (ok && t == 0) ? p[288 + wt] : 0u;
    R.v[nt][0] = ok ? p[576 + 9 * h + t] : 0u; R.v[nt][1] = ok ? p[576 + 9 * h + 4 + t] : 0u;
    R.v[nt][2] = (ok && t == 0) ? p[576 + 9 * h + 8] : 0u;
  }
}
__device__ __noinline__ void attention(int row0, int role, int m, int aw, int lane) {
  if (lane < 8) flag_wait(&g_flags[m * 8 + lane], 1, 5);
  else if (lane < 16 && role == 0 && m > 0) flag_wait(&g_flags[(m - 1) * 8 + lane - 8], 1, 5);
  __syncwarp();
  if (aw == 0 && lane == 0) TS2(24);
  const float scale = 0.23570226039551584f;
  const int g = lane >> 2, t = lane & 3;
  const int qrow = row0 + role * 16;
  HeadRegs N;
  load_head(N, aw, qrow, g, t);
#pragma unroll 1
  for (int h = aw; h < 32; h += 8) {
    HeadRegs R = N;
    if (h + 8 < 32) load_head(N, h + 8, qrow, g, t);
    float sc[4][4];
#pragma unroll
    for (int nt = 0; nt < 4; ++nt) {
      sc[nt][0] = sc[nt][1] = sc[nt][2] = sc[nt][3] = 0.f;
      mma16816(sc[nt], R.q[0][0], R.q[1][0], R.q[0][1], R.q[1][1], R.k[nt][0], R.k[nt][1]);
      mma16816(sc[nt], R.q[0][2], R.q[1][2], 0u, 0u, R.k[nt][2], 0u);
    }
    const int par = g & 1;
    float l0[4], l1[4];
    float mx0 = -3.0e38f, mx1 = -3.0e38f;
#pragma unroll
    for (int nt = 0; nt < 4; ++nt) {
      const int jj = 8 * nt + 2 * t + par;
      const int d0 = g + 14 - jj, d1 = d0 + 8;
      const bool inr = qrow - 14 + jj >= 0;
      const bool ok0 = inr && d0 >= 0 && d0 <= 14, ok1 = inr && d1 >= 0 && d1 <= 14;
      uint32_t pk = pack_bf16(par ? sc[nt][1] : sc[nt][0], par ? sc[nt][3] : sc[nt][2]);
      pk = pack_bf16(__uint_as_float(pk << 16) * scale, __uint_as_float(pk & 0xffff0000u) * scale);
      l0[nt] = ok0 ? __uint_as_float(pk << 16) : -3.0e38f;
      l1[nt] = ok1 ? __uint_as_float(pk & 0xffff0000u) : -3.0e38f;
      mx0 = fmaxf(mx0, l0[nt]); mx1 = fmaxf(mx1, l1[nt]);
    }
    mx0 = fmaxf(mx0, __shfl_xor_sync(0xffffffffu, mx0, 1)); mx0 = fmaxf(mx0, __shfl_xor_sync(0xffffffffu, mx0, 2));
    mx1 = fmaxf(mx1, __shfl_xor_sync(0xffffffffu, mx1, 1)); mx1 = fmaxf(mx1, __shfl_xor_sync(0xffffffffu, mx1, 2));
    float s0 = 0.f, s1 = 0.f;
#pragma unroll
    for (int nt = 0; nt < 4; ++nt) {
      l0[nt] = __expf(l0[nt] - mx0); l1[nt] = __expf(l1[nt] - mx1);
      s0 += l0[nt]; s1 += l1[nt];
    }
    s0 += __shfl_xor_sync(0xffffffffu, s0, 1); s0 += __shfl_xor_sync(0xffffffffu, s0, 2);
    s1 += __shfl_xor_sync(0xffffffffu, s1, 1); s1 += __shfl_xor_sync(0xffffffffu, s1, 2);
    const float i0 = __frcp_rn(s0), i1 = __frcp_rn(s1);
    uint32_t pa[2][4];
#pragma unroll
    for (int nt = 0; nt < 4; ++nt) {
      const float p0 = l0[nt] * i0, p1 = l1[nt] * i1;
      pa[nt >> 1][(nt & 1) * 2] = par ? pack_bf16(0.f, p0) : pack_bf16(p0, 0.f);
      pa[nt >> 1][(nt & 1) * 2 + 1] = par ? pack_bf16(0.f, p1) : pack_bf16(p1, 0.f);
    }
    uint32_t* o0p = (uint32_t*)(g_act + (size_t)(qrow + g) * ACT_) + 9 * h;
    uint32_t* o1p = (uint32_t*)(g_act + (size_t)(qrow + g + 8) * ACT_) + 9 * h;
#pragma unroll
    for (int cg = 0; cg < 3; ++cg) {
      float oc[4] = {0.f, 0.f, 0.f, 0.f};
      mma16816(oc, pa[0][0], pa[0][1], pa[0][2], pa[0][3], movm(R.v[0][cg]), movm(R.v[1][cg]));
      mma16816(oc, pa[1][0], pa[1][1], pa[1][2], pa[1][3], movm(R.v[2][cg]), movm(R.v[3][cg]));
      if (cg < 2 || t == 0) {
        o0p[4 * cg + t] = pack_bf16(oc[0], oc[1]);
        o1p[4 * cg + t] = pack_bf16(oc[2], oc[3]);
      }
    }
  }
  if (aw == 0 && lane == 0) TS2(26);
}

__device__ __noinline__ void tail_exchange(const uint8_t* sgen, int t256, int m, int j, int p, const __nv_bfloat16* __restrict__ x, __nv_bfloat16* __restrict__ out) {
  const int nch = j ? 32 : 40, lane = t256 & 31, row0 = m * 128, ncol0 = j ? 320 : 0;
  const uint32_t pitch = nch * 32 + 32;
    {
      uint4* xs = g_xch + (size_t)((m * 2 + j) * 4) * 128 * 40;
      unsigned* pf = &g_flags[144 + (m * 2 + j) * 4];
#pragma unroll 5
      for (int e = t256; e < 96 * nch; e += 256) {
        int r = e / nch, cI = e - r * nch;
        r += (r >= 32 * p) ? 32 : 0;
        const float4 u0 = *(const float4*)(sgen + r * pitch + cI * 32), u1 = *(const float4*)(sgen + r * pitch + cI * 32 + 16);
        xs[((size_t)p * 128 + r) * 40 + cI] = make_uint4(pack_bf16(u0.x, u0.y), pack_bf16(u0.z, u0.w), pack_bf16(u1.x, u1.y), pack_bf16(u1.z, u1.w));
      }
      if (t256 == 0) TS2(61);
      __threadfence();
      __syncwarp();
      if (t256 == 0) TS2(62);
      if (lane < 4 && lane != p) flag_add(pf + lane);
      if (lane == 0) flag_wait(pf + p, 24, 6);
      __syncwarp();
      if (t256 == 0) TS(9);
      const int nit = nch >> 3;
      uint4 v[5][4];
#pragma unroll
      for (int i = 0; i < 5; ++i) {
        if (i < nit) {
          const int e = t256 + i * 256;
          const int rl = e / nch, cI = e - rl * nch, r = 32 * p + rl;
#pragma unroll
          for (int k = 0; k < 3; ++k) v[i][k] = __ldcg(xs + ((size_t)(k + (k >= p)) * 128 + r) * 40 + cI);
          v[i][3] = __ldg((const uint4*)(x + (size_t)(row0 + r) * D_ + ncol0 + cI * 8));
        }
      }
#pragma unroll
      for (int i = 0; i < 5; ++i) {
        if (i < nit) {
          const int e = t256 + i * 256;
          const int rl = e / nch, cI = e - rl * nch, r = 32 * p + rl;
          const float4 u0 = *(const float4*)(sgen + r * pitch + cI * 32), u1 = *(const float4*)(sgen + r * pitch + cI * 32 + 16);
          float f[8] = {u0.x, u0.y, u0.z, u0.w, u1.x, u1.y, u1.z, u1.w};
          uint32_t o[4];
#pragma unroll
          for (int e2 = 0; e2 < 4; ++e2) {
            const uint32_t w0 = ((const uint32_t*)&v[i][0])[e2], w1 = ((const uint32_t*)&v[i][1])[e2], w2 = ((const uint32_t*)&v[i][2])[e2], w3 = ((const uint32_t*)&v[i][3])[e2];
            float lo = f[2 * e2] + ((__uint_as_float(w0 << 16) + __uint_as_float(w1 << 16)) + (__uint_as_float(w2 << 16) + __uint_as_float(w3 << 16)));
            float hi = f[2 * e2 + 1] + ((__uint_as_float(w0 & 0xffff0000u) + __uint_as_float(w1 & 0xffff0000u)) + (__uint_as_float(w2 & 0xffff0000u) + __uint_as_float(w3 & 0xffff0000u)));
            o[e2] = pack_bf16(lo, hi);
          }
          *(uint4*)(out + (size_t)(row0 + r) * D_ + ncol0 + cI * 8) = make_uint4(o[0], o[1], o[2], o[3]);
        }
      }
      if (t256 == 0) TS(10);
    }
}

__global__ void __cluster_dims__(2, 1, 1) __launch_bounds__(384, 1)
fused_kernel(const __grid_constant__ CUtensorMap m_qkv1, const __grid_constant__ CUtensorMap m_qkv2,
             const __grid_constant__ CUtensorMap m_gate2, const __grid_constant__ CUtensorMap m_up2,
             const __grid_constant__ CUtensorMap m_wo5, const __grid_constant__ CUtensorMap m_wo4,
             const __grid_constant__ CUtensorMap m_down5, const __grid_constant__ CUtensorMap m_down4,
             const __grid_constant__ CUtensorMap m_act,
             const __nv_bfloat16* __restrict__ x, __nv_bfloat16* __restrict__ out) {
  extern __shared__ uint8_t smem_raw[];
  const uint32_t sbase = (smem_u32(smem_raw) + 1023) & ~1023u;
  const uint32_t bars = sbase + DATA_BYTES;
  const uint32_t full1 = bars, empty1 = bars + 64, full2 = bars + 128, empty2 = bars + 192, pub = bars + 256;
  const int rank = blockIdx.x & 1, cl = blockIdx.x >> 1;
  const int role = cl & 7, m = (cl >> 3) * 2 + rank, p = role >> 1, j = role & 1;
  const int row0 = m * 128;
  const int warp = __shfl_sync(0xffffffffu, (int)(threadIdx.x >> 5), 0), lane = threadIdx.x & 31;
  const int nkb2 = (p == 3) ? 21 : 20;
  const int nblk2 = j ? 4 : 5;
  const int ncol0 = j ? 320 : 0;

  uint4 nx[9];
  if (warp >= 4) {
    const int cw = warp - 4;
    const uint4* src = (const uint4*)(x + (size_t)(row0 + cw * 16 + (lane >> 3)) * D_) + (lane & 7);
#pragma unroll
    for (int t = 0; t < 9; ++t) nx[t] = __ldg(src + 8 * t);
  }
  if (threadIdx.x == 0) {
    for (int s = 0; s < NS1; ++s) { mbar_init(full1 + 8 * s, 1); mbar_init(empty1 + 8 * s, MC ? 4 : 2); }
    for (int s = 0; s < NS2; ++s) { mbar_init(full2 + 8 * s, 1); mbar_init(empty2 + 8 * s, MC ? 4 : 2); }
    for (int s = 0; s < 7; ++s) mbar_init(pub + 8 * s, 256);
    asm volatile("fence.mbarrier_init.release.cluster;" ::: "memory");
  }
  __syncthreads();
  cluster_sync();

  if (warp < 4) {
    asm volatile("setmaxnreg.dec.sync.aligned.u32 40;");
    if (warp == 0) {
      if (lane == 0) {
        uint32_t it = 0;
        const int nt = num_tiles(j);
        volatile uint32_t* known = (volatile uint32_t*)(smem_raw + (bars + 320 - smem_u32(smem_raw)));
        volatile uint32_t* sched = known + 12;
        for (int t = 0; t < nt; ++t) {
          Tile T = get_tile(p, j, t);
          const CUtensorMap* mp; int cb, nmine;
          if (T.is_h) { mp = rank ? &m_up2 : &m_gate2; cb = T.col >> 6; nmine = 2; }
          else if (T.nb == 4) { mp = &m_qkv2; cb = (T.col >> 6) + 2 * rank; nmine = 2; }
          else if (T.nb == 3) { mp = rank ? &m_qkv1 : &m_qkv2; cb = (T.col >> 6) + 2 * rank; nmine = rank ? 1 : 2; }
          else { mp = &m_qkv1; cb = (T.col >> 6) + rank; nmine = 1; }
          const uint32_t doff = (T.nb == 2 ? rank : 2 * rank) * 4096;
          for (int kb = 0; kb < 18; ++kb, ++it) {
            uint32_t s = it % NS1, ph = (it / NS1) & 1;
            if (it == 5) {
              for (int r = 0; r < 9; ++r) known[r] = 0;
              const int hlo = p == 0 ? 0 : 20 * p - 9, hhi = 20 * p + 11 + (p == 3 ? 1 : 0);
              int n = 0;
              for (int tt = 1; tt <= 5; ++tt)
                for (int hb = hlo; hb < hhi; ++hb) {
                  int TT = hb >> 1, pp = TT / 9, idx = TT - 9 * pp;
                  int ot = 1 + (idx >= 4 ? idx - 4 : idx);
                  if (ot == tt) sched[n++] = (uint32_t)hb | ((uint32_t)(2 * pp + (idx >= 4)) << 8) | ((uint32_t)(ot + 1) << 16);
                }
            }
            mbar_wait(empty1 + 8 * s, s >= 5 ? ph : ph ^ 1, 1);
            mbar_expect_tx(full1 + 8 * s, T.nb * 4096);
            tma_load_3d_mc(sbase + slot1_off(s) + doff, mp, 0, kb * 32, cb, full1 + 8 * s, 3);
            (void)nmine;
          }
        }
        const CUtensorMap* mwo = j ? &m_wo4 : &m_wo5;
        const CUtensorMap* mdn = j ? &m_down4 : &m_down5;
        for (int i = 0; i < nkb2; ++i) {
          uint32_t s = i % NS2, ph = (i / NS2) & 1;
          int acol, kn, wrow; const CUtensorMap* mp; const unsigned* fl; unsigned tgt;
          if (p == 0 && i >= 11) {
            acol = (i - 11) * 64; mp = mwo; wrow = acol; fl = &g_flags[128 + m]; tgt = 8; kn = 8;
          } else {
            uint32_t e = sched[i];
            wrow = (e & 255) * 64; kn = (e >> 8) & 255; tgt = e >> 16;
            acol = 576 + wrow; mp = mdn; fl = &g_flags[m * 8 + kn];
          }
          mbar_wait(empty2 + 8 * s, ph, 2);
          mbar_expect_tx(full2 + 8 * s, 16384 + nblk2 * 8192);
          uint32_t dst = sbase + s * ST2_BYTES;
          tma_load_3d_mc(dst + 16384 + rank * nblk2 * 4096, mp, 0, wrow + 32 * rank, ncol0 >> 6, full2 + 8 * s, 3);
          if (known[kn] < tgt) { known[kn] = flag_wait(fl, tgt, 4); fence_proxy_async(); }
          tma_load_2d(dst, &m_act, acol, row0, full2 + 8 * s);
          TS2(32 + i);
        }
        agent_exit();
      }
    } else if (warp == 1) {
      const int nt = num_tiles(j);
      for (int t = 0; t < nt; ++t) {
        mbar_wait(pub + 8 * t, 0, 7);
        if (lane == 0) { if (t == 0) TS2(27); __threadfence(); flag_add(&g_flags[m * 8 + role]); if (t == 0) TS2(28); }
        __syncwarp();
        if (t == 1) {
          mbar_wait(pub + 8 * 6, 0, 7);
          if (lane == 0) { __threadfence(); flag_add(&g_flags[128 + m]); }
          __syncwarp();
        }
      }
      if (lane == 0) agent_exit();
    } else if (warp == 2) {
      if (lane == 0) {
        const int mp8 = cl >> 3, nt = num_tiles(j);
        for (int t = 1; t <= nt; ++t) {
          if (t >= 2) mbar_wait(pub + 8 * (t - 2), 0, 7);
          if (t < nt) {
            Tile T = get_tile(p, j, t);
            for (int kb = mp8; kb < 18; kb += 8) tma_prefetch_3d(rank ? &m_up2 : &m_gate2, 0, kb * 32, T.col >> 6);
          } else {
            const int hlo = p == 0 ? 0 : 20 * p - 9, hhi = 20 * p + 11 + (p == 3 ? 1 : 0);
            for (int hb = hlo + mp8; hb < hhi; hb += 8) tma_prefetch_3d(j ? &m_down4 : &m_down5, 0, hb * 64 + 32 * rank, ncol0 >> 6);
            if (p == 0) for (int ob = mp8; ob < 9; ob += 8) tma_prefetch_3d(j ? &m_wo4 : &m_wo5, 0, ob * 64 + 32 * rank, ncol0 >> 6);
          }
        }
      }
    }
  } else {
    asm volatile("setmaxnreg.inc.sync.aligned.u32 232;");
    Ctx c;
    c.sbase = sbase; c.full1 = full1; c.empty1 = empty1; c.full2 = full2; c.empty2 = empty2; c.peer = rank ^ 1;
    c.wg = (warp - 4) >> 2; c.tid = threadIdx.x - 128 - c.wg * 128;
    const int w = c.tid >> 5;
    if (c.wg == 0 && c.tid == 0) TS(0);
    uint32_t areg[8][4];
    {
      const int sub = lane >> 3, li = lane & 7;
#pragma unroll 1
      for (int itr = 0; itr < 4; ++itr) {
        const int r = c.wg * 64 + w * 16 + itr * 4 + sub;
        uint4 xv[9];
#pragma unroll
        for (int t = 0; t < 9; ++t) xv[t] = nx[t];
        if (itr < 3) {
          const uint4* src = (const uint4*)(x + (size_t)(row0 + r + 4) * D_) + li;
#pragma unroll
          for (int t = 0; t < 9; ++t) nx[t] = __ldg(src + 8 * t);
        }
        float s0 = 0.f, s1 = 0.f;
#pragma unroll
        for (int t = 0; t < 9; ++t) {
          const uint32_t* u = (const uint32_t*)&xv[t];
#pragma unroll
          for (int e = 0; e < 4; ++e) { s0 += __uint_as_float(u[e] << 16); s1 += __uint_as_float(u[e] & 0xffff0000u); }
        }
        float sum = s0 + s1;
        sum += __shfl_xor_sync(0xffffffffu, sum, 1); sum += __shfl_xor_sync(0xffffffffu, sum, 2); sum += __shfl_xor_sync(0xffffffffu, sum, 4);
        const float mean = sum * (1.f / 576.f);
        float q0 = 0.f, q1 = 0.f;
#pragma unroll
        for (int t = 0; t < 9; ++t) {
          const uint32_t* u = (const uint32_t*)&xv[t];
#pragma unroll
          for (int e = 0; e < 4; ++e) {
            float a = __uint_as_float(u[e] << 16) - mean, b = __uint_as_float(u[e] & 0xffff0000u) - mean;
            q0 = fmaf(a, a, q0); q1 = fmaf(b, b, q1);
          }
        }
        float sq = q0 + q1;
        sq += __shfl_xor_sync(0xffffffffu, sq, 1); sq += __shfl_xor_sync(0xffffffffu, sq, 2); sq += __shfl_xor_sync(0xffffffffu, sq, 4);
        const float vb = bf16r(sq * (1.f / 576.f));
        const float rinv = 1.f / bf16r(sqrtf(bf16r(vb + 1e-5f)));
        const __nv_bfloat162 mb2 = __float2bfloat162_rn(mean);
        const uint32_t dsta = sbase + r * 128 + ((li ^ (r & 7)) << 4);
#pragma unroll
        for (int t = 0; t < 9; ++t) {
          const uint32_t* u = (const uint32_t*)&xv[t];
          uint32_t o[4];
#pragma unroll
          for (int e = 0; e < 4; ++e) {
            __nv_bfloat162 d2 = __hsub2(*(const __nv_bfloat162*)&u[e], mb2);
            uint32_t du = *(uint32_t*)&d2;
            o[e] = pack_bf16(__uint_as_float(du << 16) * rinv, __uint_as_float(du & 0xffff0000u) * rinv);
          }
          asm volatile("st.shared.v4.b32 [%0], {%1, %2, %3, %4};" ::"r"(dsta + t * 16384), "r"(o[0]), "r"(o[1]), "r"(o[2]), "r"(o[3]) : "memory");
        }
      }
      asm volatile("fence.proxy.async.shared::cta;" ::: "memory");
      __syncwarp();
      {
        const int r = c.wg * 64 + w * 16 + (lane & 7) + ((lane >> 3) & 1) * 8;
        const int hi = lane >> 4;
#pragma unroll
        for (int ks = 0; ks < 8; ++ks) {
          const uint32_t ad = sbase + (7 + (ks >> 2)) * 16384 + r * 128 + ((((ks & 3) * 2 + hi) ^ (r & 7)) << 4);
          asm volatile("ldmatrix.sync.aligned.m8n8.x4.shared.b16 {%0, %1, %2, %3}, [%4];"
                       : "=r"(areg[ks][0]), "=r"(areg[ks][1]), "=r"(areg[ks][2]), "=r"(areg[ks][3]) : "r"(ad) : "memory");
        }
      }
      named_bar(1 + c.wg, 128);
      if (c.tid == 0) { mbar_arrive_both(empty1 + 8 * 5); mbar_arrive_both(empty1 + 8 * 6); }
      if (c.wg == 1) {
        const long long t0 = clock64();
        while (clock64() - t0 < SKEW) {}
      }
    }
    if (c.wg == 0 && c.tid == 0) TS(1);
    unsigned* myflag = &g_flags[m * 8 + role];
    {
      uint32_t it = 0;
      const int nt = num_tiles(j);
#pragma unroll 1
      for (int t = 0; t < nt; ++t) {
        Tile T = get_tile(p, j, t);
        if (T.nb == 4) {
          float acc[128] = {};
          g1_tile<4>(c, acc, it, areg);
          if (T.is_h) epi_h<4>(c, acc, row0, T.col); else epi_qkv<4>(c, acc, row0, T.col);
        } else if (T.nb == 3) {
          float acc[96] = {};
          g1_tile<3>(c, acc, it, areg);
          epi_qkv<3>(c, acc, row0, T.col);
        } else {
          float acc[64] = {};
          g1_tile<2>(c, acc, it, areg);
          epi_qkv<2>(c, acc, row0, T.col);
        }
        if (t == nt - 1 && c.tid == 0) {
          for (int s = 0; s < NS2; ++s) { mbar_arrive_both(empty2 + 8 * s); }
        }
        mbar_arrive_local(pub + 8 * t);
        if (t == 1) {
          if (c.wg == 0 && c.tid == 0) TS(11);
          attention(row0, role, m, c.wg * 4 + w, lane);
          mbar_arrive_local(pub + 8 * 6);
          if (c.wg == 0 && c.tid == 0) TS(12);
        }
        if (c.wg == 0 && c.tid == 0) TS(2 + t);
      }
    }
    const int nch = j ? 32 : 40;
    const uint32_t pitch = nch * 32 + 32;
    const uint32_t sacc = sbase + (c.wg * 64 + w * 16 + (lane >> 2)) * pitch + (lane & 3) * 8;
    if (j == 0) {
      float acc1[96] = {}, acc2[64] = {};
      wgmma_fence();
#pragma unroll 1
      for (int i = 0; i < nkb2; ++i) {
        uint32_t s = i % NS2, ph = (i / NS2) & 1;
        mbar_wait(full2 + 8 * s, ph, 3);
        if (c.wg == 0 && c.tid == 0) TS2(i);
        uint32_t a0 = sbase + s * ST2_BYTES + c.wg * 8192, b0 = sbase + s * ST2_BYTES + 16384;
        wgmma_fence();
#pragma unroll
        for (int k = 0; k < 4; ++k) {
          uint64_t da = make_desc(a0 + k * 32, 16, 1024);
          const uint32_t bk = b0 + (k >> 1) * (5 * 4096) + (k & 1) * 2048;
          wgmma_n192(acc1, da, make_desc(bk, 4096, 1024), (i | k) != 0);
          wgmma_n128(acc2, da, make_desc(bk + 3 * 4096, 4096, 1024), (i | k) != 0);
        }
        wgmma_commit();
        if (i > 0) {
          wgmma_wait<1>();
          if (c.tid == 0 && i - 1 + NS2 < nkb2) { uint32_t sp = (i - 1) % NS2; mbar_arrive_both(empty2 + 8 * sp); }
        }
      }
      wgmma_wait<0>();
      if (c.wg == 0 && c.tid == 0) TS(8);
      named_bar(3, 256);
      acc_to_smem<96>(acc1, sacc, pitch);
      acc_to_smem<64>(acc2, sacc + 768, pitch);
    } else {
      float acc[128] = {};
      wgmma_fence();
#pragma unroll 1
      for (int i = 0; i < nkb2; ++i) {
        uint32_t s = i % NS2, ph = (i / NS2) & 1;
        mbar_wait(full2 + 8 * s, ph, 3);
        if (c.wg == 0 && c.tid == 0) TS2(i);
        uint32_t a0 = sbase + s * ST2_BYTES + c.wg * 8192, b0 = sbase + s * ST2_BYTES + 16384;
        wgmma_fence();
#pragma unroll
        for (int k = 0; k < 4; ++k)
          wgmma_n256(acc, make_desc(a0 + k * 32, 16, 1024), make_desc(b0 + (k >> 1) * (4 * 4096) + (k & 1) * 2048, 4096, 1024), (i | k) != 0);
        wgmma_commit();
        if (i > 0) {
          wgmma_wait<1>();
          if (c.tid == 0 && i - 1 + NS2 < nkb2) { uint32_t sp = (i - 1) % NS2; mbar_arrive_both(empty2 + 8 * sp); }
        }
      }
      wgmma_wait<0>();
      if (c.wg == 0 && c.tid == 0) TS(8);
      named_bar(3, 256);
      acc_to_smem<128>(acc, sacc, pitch);
    }
    named_bar(3, 256);
    if (c.wg == 0 && c.tid == 0) TS2(60);
    tail_exchange(smem_raw + (sbase - smem_u32(smem_raw)), c.wg * 128 + c.tid, m, j, p, x, out);
    named_bar(1 + c.wg, 128);
    if (c.tid == 0) agent_exit();
  }
}

typedef CUresult (*EncodeFn)(CUtensorMap*, CUtensorMapDataType, cuuint32_t, void*, const cuuint64_t*, const cuuint64_t*,
                             const cuuint32_t*, const cuuint32_t*, CUtensorMapInterleave, CUtensorMapSwizzle,
                             CUtensorMapL2promotion, CUtensorMapFloatOOBfill);

static void make_map2(EncodeFn enc, CUtensorMap* mp, const void* ptr, int rows, int cols, int box_rows) {
  cuuint64_t dims[2] = {(cuuint64_t)cols, (cuuint64_t)rows};
  cuuint64_t strides[1] = {(cuuint64_t)cols * 2};
  cuuint32_t box[2] = {64, (cuuint32_t)box_rows};
  cuuint32_t es[2] = {1, 1};
  enc(mp, CU_TENSOR_MAP_DATA_TYPE_BFLOAT16, 2, (void*)ptr, dims, strides, box, es, CU_TENSOR_MAP_INTERLEAVE_NONE,
      CU_TENSOR_MAP_SWIZZLE_128B, CU_TENSOR_MAP_L2_PROMOTION_L2_256B, CU_TENSOR_MAP_FLOAT_OOB_FILL_NONE);
}
static void make_map3(EncodeFn enc, CUtensorMap* mp, const void* ptr, int rows, int cols, int nblk) {
  cuuint64_t dims[3] = {64, (cuuint64_t)rows, (cuuint64_t)(cols / 64)};
  cuuint64_t strides[2] = {(cuuint64_t)cols * 2, 128};
  cuuint32_t box[3] = {64, 32, (cuuint32_t)nblk};
  cuuint32_t es[3] = {1, 1, 1};
  enc(mp, CU_TENSOR_MAP_DATA_TYPE_BFLOAT16, 3, (void*)ptr, dims, strides, box, es, CU_TENSOR_MAP_INTERLEAVE_NONE,
      CU_TENSOR_MAP_SWIZZLE_128B, CU_TENSOR_MAP_L2_PROMOTION_L2_256B, CU_TENSOR_MAP_FLOAT_OOB_FILL_NONE);
}

extern "C" void kernel_launch(void* const* d_in, const int* in_sizes, int n_in, void* d_out, int out_size) {
  static EncodeFn enc = nullptr;
  static void* act_ptr = nullptr;
  if (!enc) {
    void* fn = nullptr;
    cudaDriverEntryPointQueryResult qr;
    cudaGetDriverEntryPoint("cuTensorMapEncodeTiled", &fn, cudaEnableDefault, &qr);
    enc = (EncodeFn)fn;
    cudaGetSymbolAddress(&act_ptr, g_act);
    cudaFuncSetAttribute(fused_kernel, cudaFuncAttributeMaxDynamicSharedMemorySize, SMEM_BYTES);
  }
  const __nv_bfloat16* x = (const __nv_bfloat16*)d_in[0];
  CUtensorMap m_qkv1, m_qkv2, m_gate2, m_up2, m_wo5, m_wo4, m_down5, m_down4, m_act;
  make_map3(enc, &m_qkv1, d_in[1], D_, QKV_, 1);
  make_map3(enc, &m_qkv2, d_in[1], D_, QKV_, 2);
  make_map3(enc, &m_gate2, d_in[4], D_, F_, 2);
  make_map3(enc, &m_up2, d_in[5], D_, F_, 2);
  make_map3(enc, &m_wo5, d_in[2], D_, D_, 5);
  make_map3(enc, &m_wo4, d_in[2], D_, D_, 4);
  make_map3(enc, &m_down5, d_in[6], F_, D_, 5);
  make_map3(enc, &m_down4, d_in[6], F_, D_, 4);
  make_map2(enc, &m_act, act_ptr, S_, ACT_, 128);
  fused_kernel<<<128, 384, SMEM_BYTES>>>(m_qkv1, m_qkv2, m_gate2, m_up2, m_wo5, m_wo4, m_down5, m_down4, m_act, x, (__nv_bfloat16*)d_out);
}
```

```cpp
#include <cuda_runtime.h>
#include <cuda_bf16.h>
#include <cuda.h>
#include <stdint.h>

constexpr int S_ = 2048, D_ = 576, F_ = 4608, QKV_ = 1728, ACT_ = 5184;
constexpr int NS1 = 7;
constexpr int NS2 = 4;
constexpr int XN_BYTES = 9 * 16384;
constexpr int RING1_OFF = 7 * 16384;
__device__ __forceinline__ uint32_t slot1_off(uint32_t s) { return RING1_OFF + (s >= 5 ? s - 5 : s + 2) * 16384; }
constexpr int ST1_BYTES = 16384;
constexpr int ST2_BYTES = 57344;
constexpr int DATA_BYTES = 229376;
constexpr int SMEM_BYTES = DATA_BYTES + 1024 + 512;
constexpr int NAGENTS = 128 * 4;
#define SKEW 0
#define MC 1

__device__ __align__(1024) __nv_bfloat16 g_qkv[S_ * QKV_];
__device__ __align__(1024) __nv_bfloat16 g_act[S_ * ACT_];
__device__ __align__(1024) __nv_bfloat16 g_part[4 * S_ * D_];
__device__ unsigned int g_flags[288];
#define TS(i)
#define TS2(i)
#define FAIL(code) __trap()
#define SPIN_MAX (1u << 24)

__device__ __forceinline__ void wgmma_n128(float (&d)[64], uint64_t da, uint64_t db, int scale_d) {
  asm volatile("{\n.reg .pred p;\nsetp.ne.b32 p, %66, 0;\n"
    "wgmma.mma_async.sync.aligned.m64n128k16.f32.bf16.bf16 {%0, %1, %2, %3, %4, %5, %6, %7, %8, %9, %10, %11, %12, %13, %14, %15, %16, %17, %18, %19, %20, %21, %22, %23, %24, %25, %26, %27, %28, %29, %30, %31, %32, %33, %34, %35, %36, %37, %38, %39, %40, %41, %42, %43, %44, %45, %46, %47, %48, %49, %50, %51, %52, %53, %54, %55, %56, %57, %58, %59, %60, %61, %62, %63}, %64, %65, p, 1, 1, 0, 1;\n}\n"
    : "+f"(d[0]), "+f"(d[1]), "+f"(d[2]), "+f"(d[3]), "+f"(d[4]), "+f"(d[5]), "+f"(d[6]), "+f"(d[7]), "+f"(d[8]), "+f"(d[9]), "+f"(d[10]), "+f"(d[11]), "+f"(d[12]), "+f"(d[13]), "+f"(d[14]), "+f"(d[15]), "+f"(d[16]), "+f"(d[17]), "+f"(d[18]), "+f"(d[19]), "+f"(d[20]), "+f"(d[21]), "+f"(d[22]), "+f"(d[23]), "+f"(d[24]), "+f"(d[25]), "+f"(d[26]), "+f"(d[27]), "+f"(d[28]), "+f"(d[29]), "+f"(d[30]), "+f"(d[31]), "+f"(d[32]), "+f"(d[33]), "+f"(d[34]), "+f"(d[35]), "+f"(d[36]), "+f"(d[37]), "+f"(d[38]), "+f"(d[39]), "+f"(d[40]), "+f"(d[41]), "+f"(d[42]), "+f"(d[43]), "+f"(d[44]), "+f"(d[45]), "+f"(d[46]), "+f"(d[47]), "+f"(d[48]), "+f"(d[49]), "+f"(d[50]), "+f"(d[51]), "+f"(d[52]), "+f"(d[53]), "+f"(d[54]), "+f"(d[55]), "+f"(d[56]), "+f"(d[57]), "+f"(d[58]), "+f"(d[59]), "+f"(d[60]), "+f"(d[61]), "+f"(d[62]), "+f"(d[63])
    : "l"(da), "l"(db), "r"(scale_d));
}

__device__ __forceinline__ void wgmma_n192(float (&d)[96], uint64_t da, uint64_t db, int scale_d) {
  asm volatile("{\n.reg .pred p;\nsetp.ne.b32 p, %98, 0;\n"
    "wgmma.mma_async.sync.aligned.m64n192k16.f32.bf16.bf16 {%0, %1, %2, %3, %4, %5, %6, %7, %8, %9, %10, %11, %12, %13, %14, %15, %16, %17, %18, %19, %20, %21, %22, %23, %24, %25, %26, %27, %28, %29, %30, %31, %32, %33, %34, %35, %36, %37, %38, %39, %40, %41, %42, %43, %44, %45, %46, %47, %48, %49, %50, %51, %52, %53, %54, %55, %56, %57, %58, %59, %60, %61, %62, %63, %64, %65, %66, %67, %68, %69, %70, %71, %72, %73, %74, %75, %76, %77, %78, %79, %80, %81, %82, %83, %84, %85, %86, %87, %88, %89, %90, %91, %92, %93, %94, %95}, %96, %97, p, 1, 1, 0, 1;\n}\n"
    : "+f"(d[0]), "+f"(d[1]), "+f"(d[2]), "+f"(d[3]), "+f"(d[4]), "+f"(d[5]), "+f"(d[6]), "+f"(d[7]), "+f"(d[8]), "+f"(d[9]), "+f"(d[10]), "+f"(d[11]), "+f"(d[12]), "+f"(d[13]), "+f"(d[14]), "+f"(d[15]), "+f"(d[16]), "+f"(d[17]), "+f"(d[18]), "+f"(d[19]), "+f"(d[20]), "+f"(d[21]), "+f"(d[22]), "+f"(d[23]), "+f"(d[24]), "+f"(d[25]), "+f"(d[26]), "+f"(d[27]), "+f"(d[28]), "+f"(d[29]), "+f"(d[30]), "+f"(d[31]), "+f"(d[32]), "+f"(d[33]), "+f"(d[34]), "+f"(d[35]), "+f"(d[36]), "+f"(d[37]), "+f"(d[38]), "+f"(d[39]), "+f"(d[40]), "+f"(d[41]), "+f"(d[42]), "+f"(d[43]), "+f"(d[44]), "+f"(d[45]), "+f"(d[46]), "+f"(d[47]), "+f"(d[48]), "+f"(d[49]), "+f"(d[50]), "+f"(d[51]), "+f"(d[52]), "+f"(d[53]), "+f"(d[54]), "+f"(d[55]), "+f"(d[56]), "+f"(d[57]), "+f"(d[58]), "+f"(d[59]), "+f"(d[60]), "+f"(d[61]), "+f"(d[62]), "+f"(d[63]), "+f"(d[64]), "+f"(d[65]), "+f"(d[66]), "+f"(d[67]), "+f"(d[68]), "+f"(d[69]), "+f"(d[70]), "+f"(d[71]), "+f"(d[72]), "+f"(d[73]), "+f"(d[74]), "+f"(d[75]), "+f"(d[76]), "+f"(d[77]), "+f"(d[78]), "+f"(d[79]), "+f"(d[80]), "+f"(d[81]), "+f"(d[82]), "+f"(d[83]), "+f"(d[84]), "+f"(d[85]), "+f"(d[86]), "+f"(d[87]), "+f"(d[88]), "+f"(d[89]), "+f"(d[90]), "+f"(d[91]), "+f"(d[92]), "+f"(d[93]), "+f"(d[94]), "+f"(d[95])
    : "l"(da), "l"(db), "r"(scale_d));
}

__device__ __forceinline__ void wgmma_n256(float (&d)[128], uint64_t da, uint64_t db, int scale_d) {
  asm volatile("{\n.reg .pred p;\nsetp.ne.b32 p, %130, 0;\n"
    "wgmma.mma_async.sync.aligned.m64n256k16.f32.bf16.bf16 {%0, %1, %2, %3, %4, %5, %6, %7, %8, %9, %10, %11, %12, %13, %14, %15, %16, %17, %18, %19, %20, %21, %22, %23, %24, %25, %26, %27, %28, %29, %30, %31, %32, %33, %34, %35, %36, %37, %38, %39, %40, %41, %42, %43, %44, %45, %46, %47, %48, %49, %50, %51, %52, %53, %54, %55, %56, %57, %58, %59, %60, %61, %62, %63, %64, %65, %66, %67, %68, %69, %70, %71, %72, %73, %74, %75, %76, %77, %78, %79, %80, %81, %82, %83, %84, %85, %86, %87, %88, %89, %90, %91, %92, %93, %94, %95, %96, %97, %98, %99, %100, %101, %102, %103, %104, %105, %106, %107, %108, %109, %110, %111, %112, %113, %114, %115, %116, %117, %118, %119, %120, %121, %122, %123, %124, %125, %126, %127}, %128, %129, p, 1, 1, 0, 1;\n}\n"
    : "+f"(d[0]), "+f"(d[1]), "+f"(d[2]), "+f"(d[3]), "+f"(d[4]), "+f"(d[5]), "+f"(d[6]), "+f"(d[7]), "+f"(d[8]), "+f"(d[9]), "+f"(d[10]), "+f"(d[11]), "+f"(d[12]), "+f"(d[13]), "+f"(d[14]), "+f"(d[15]), "+f"(d[16]), "+f"(d[17]), "+f"(d[18]), "+f"(d[19]), "+f"(d[20]), "+f"(d[21]), "+f"(d[22]), "+f"(d[23]), "+f"(d[24]), "+f"(d[25]), "+f"(d[26]), "+f"(d[27]), "+f"(d[28]), "+f"(d[29]), "+f"(d[30]), "+f"(d[31]), "+f"(d[32]), "+f"(d[33]), "+f"(d[34]), "+f"(d[35]), "+f"(d[36]), "+f"(d[37]), "+f"(d[38]), "+f"(d[39]), "+f"(d[40]), "+f"(d[41]), "+f"(d[42]), "+f"(d[43]), "+f"(d[44]), "+f"(d[45]), "+f"(d[46]), "+f"(d[47]), "+f"(d[48]), "+f"(d[49]), "+f"(d[50]), "+f"(d[51]), "+f"(d[52]), "+f"(d[53]), "+f"(d[54]), "+f"(d[55]), "+f"(d[56]), "+f"(d[57]), "+f"(d[58]), "+f"(d[59]), "+f"(d[60]), "+f"(d[61]), "+f"(d[62]), "+f"(d[63]), "+f"(d[64]), "+f"(d[65]), "+f"(d[66]), "+f"(d[67]), "+f"(d[68]), "+f"(d[69]), "+f"(d[70]), "+f"(d[71]), "+f"(d[72]), "+f"(d[73]), "+f"(d[74]), "+f"(d[75]), "+f"(d[76]), "+f"(d[77]), "+f"(d[78]), "+f"(d[79]), "+f"(d[80]), "+f"(d[81]), "+f"(d[82]), "+f"(d[83]), "+f"(d[84]), "+f"(d[85]), "+f"(d[86]), "+f"(d[87]), "+f"(d[88]), "+f"(d[89]), "+f"(d[90]), "+f"(d[91]), "+f"(d[92]), "+f"(d[93]), "+f"(d[94]), "+f"(d[95]), "+f"(d[96]), "+f"(d[97]), "+f"(d[98]), "+f"(d[99]), "+f"(d[100]), "+f"(d[101]), "+f"(d[102]), "+f"(d[103]), "+f"(d[104]), "+f"(d[105]), "+f"(d[106]), "+f"(d[107]), "+f"(d[108]), "+f"(d[109]), "+f"(d[110]), "+f"(d[111]), "+f"(d[112]), "+f"(d[113]), "+f"(d[114]), "+f"(d[115]), "+f"(d[116]), "+f"(d[117]), "+f"(d[118]), "+f"(d[119]), "+f"(d[120]), "+f"(d[121]), "+f"(d[122]), "+f"(d[123]), "+f"(d[124]), "+f"(d[125]), "+f"(d[126]), "+f"(d[127])
    : "l"(da), "l"(db), "r"(scale_d));
}

__device__ __forceinline__ void wgmma_rs_n128(float (&d)[64], const uint32_t (&a)[4], uint64_t db) {
  asm volatile(
    "wgmma.mma_async.sync.aligned.m64n128k16.f32.bf16.bf16 {%0, %1, %2, %3, %4, %5, %6, %7, %8, %9, %10, %11, %12, %13, %14, %15, %16, %17, %18, %19, %20, %21, %22, %23, %24, %25, %26, %27, %28, %29, %30, %31, %32, %33, %34, %35, %36, %37, %38, %39, %40, %41, %42, %43, %44, %45, %46, %47, %48, %49, %50, %51, %52, %53, %54, %55, %56, %57, %58, %59, %60, %61, %62, %63}, {%64, %65, %66, %67}, %68, 1, 1, 1, 1;\n"
    : "+f"(d[0]), "+f"(d[1]), "+f"(d[2]), "+f"(d[3]), "+f"(d[4]), "+f"(d[5]), "+f"(d[6]), "+f"(d[7]), "+f"(d[8]), "+f"(d[9]), "+f"(d[10]), "+f"(d[11]), "+f"(d[12]), "+f"(d[13]), "+f"(d[14]), "+f"(d[15]), "+f"(d[16]), "+f"(d[17]), "+f"(d[18]), "+f"(d[19]), "+f"(d[20]), "+f"(d[21]), "+f"(d[22]), "+f"(d[23]), "+f"(d[24]), "+f"(d[25]), "+f"(d[26]), "+f"(d[27]), "+f"(d[28]), "+f"(d[29]), "+f"(d[30]), "+f"(d[31]), "+f"(d[32]), "+f"(d[33]), "+f"(d[34]), "+f"(d[35]), "+f"(d[36]), "+f"(d[37]), "+f"(d[38]), "+f"(d[39]), "+f"(d[40]), "+f"(d[41]), "+f"(d[42]), "+f"(d[43]), "+f"(d[44]), "+f"(d[45]), "+f"(d[46]), "+f"(d[47]), "+f"(d[48]), "+f"(d[49]), "+f"(d[50]), "+f"(d[51]), "+f"(d[52]), "+f"(d[53]), "+f"(d[54]), "+f"(d[55]), "+f"(d[56]), "+f"(d[57]), "+f"(d[58]), "+f"(d[59]), "+f"(d[60]), "+f"(d[61]), "+f"(d[62]), "+f"(d[63])
    : "r"(a[0]), "r"(a[1]), "r"(a[2]), "r"(a[3]), "l"(db));
}

__device__ __forceinline__ void wgmma_rs_n192(float (&d)[96], const uint32_t (&a)[4], uint64_t db) {
  asm volatile(
    "wgmma.mma_async.sync.aligned.m64n192k16.f32.bf16.bf16 {%0, %1, %2, %3, %4, %5, %6, %7, %8, %9, %10, %11, %12, %13, %14, %15, %16, %17, %18, %19, %20, %21, %22, %23, %24, %25, %26, %27, %28, %29, %30, %31, %32, %33, %34, %35, %36, %37, %38, %39, %40, %41, %42, %43, %44, %45, %46, %47, %48, %49, %50, %51, %52, %53, %54, %55, %56, %57, %58, %59, %60, %61, %62, %63, %64, %65, %66, %67, %68, %69, %70, %71, %72, %73, %74, %75, %76, %77, %78, %79, %80, %81, %82, %83, %84, %85, %86, %87, %88, %89, %90, %91, %92, %93, %94, %95}, {%96, %97, %98, %99}, %100, 1, 1, 1, 1;\n"
    : "+f"(d[0]), "+f"(d[1]), "+f"(d[2]), "+f"(d[3]), "+f"(d[4]), "+f"(d[5]), "+f"(d[6]), "+f"(d[7]), "+f"(d[8]), "+f"(d[9]), "+f"(d[10]), "+f"(d[11]), "+f"(d[12]), "+f"(d[13]), "+f"(d[14]), "+f"(d[15]), "+f"(d[16]), "+f"(d[17]), "+f"(d[18]), "+f"(d[19]), "+f"(d[20]), "+f"(d[21]), "+f"(d[22]), "+f"(d[23]), "+f"(d[24]), "+f"(d[25]), "+f"(d[26]), "+f"(d[27]), "+f"(d[28]), "+f"(d[29]), "+f"(d[30]), "+f"(d[31]), "+f"(d[32]), "+f"(d[33]), "+f"(d[34]), "+f"(d[35]), "+f"(d[36]), "+f"(d[37]), "+f"(d[38]), "+f"(d[39]), "+f"(d[40]), "+f"(d[41]), "+f"(d[42]), "+f"(d[43]), "+f"(d[44]), "+f"(d[45]), "+f"(d[46]), "+f"(d[47]), "+f"(d[48]), "+f"(d[49]), "+f"(d[50]), "+f"(d[51]), "+f"(d[52]), "+f"(d[53]), "+f"(d[54]), "+f"(d[55]), "+f"(d[56]), "+f"(d[57]), "+f"(d[58]), "+f"(d[59]), "+f"(d[60]), "+f"(d[61]), "+f"(d[62]), "+f"(d[63]), "+f"(d[64]), "+f"(d[65]), "+f"(d[66]), "+f"(d[67]), "+f"(d[68]), "+f"(d[69]), "+f"(d[70]), "+f"(d[71]), "+f"(d[72]), "+f"(d[73]), "+f"(d[74]), "+f"(d[75]), "+f"(d[76]), "+f"(d[77]), "+f"(d[78]), "+f"(d[79]), "+f"(d[80]), "+f"(d[81]), "+f"(d[82]), "+f"(d[83]), "+f"(d[84]), "+f"(d[85]), "+f"(d[86]), "+f"(d[87]), "+f"(d[88]), "+f"(d[89]), "+f"(d[90]), "+f"(d[91]), "+f"(d[92]), "+f"(d[93]), "+f"(d[94]), "+f"(d[95])
    : "r"(a[0]), "r"(a[1]), "r"(a[2]), "r"(a[3]), "l"(db));
}

__device__ __forceinline__ void wgmma_rs_n256(float (&d)[128], const uint32_t (&a)[4], uint64_t db) {
  asm volatile(
    "wgmma.mma_async.sync.aligned.m64n256k16.f32.bf16.bf16 {%0, %1, %2, %3, %4, %5, %6, %7, %8, %9, %10, %11, %12, %13, %14, %15, %16, %17, %18, %19, %20, %21, %22, %23, %24, %25, %26, %27, %28, %29, %30, %31, %32, %33, %34, %35, %36, %37, %38, %39, %40, %41, %42, %43, %44, %45, %46, %47, %48, %49, %50, %51, %52, %53, %54, %55, %56, %57, %58, %59, %60, %61, %62, %63, %64, %65, %66, %67, %68, %69, %70, %71, %72, %73, %74, %75, %76, %77, %78, %79, %80, %81, %82, %83, %84, %85, %86, %87, %88, %89, %90, %91, %92, %93, %94, %95, %96, %97, %98, %99, %100, %101, %102, %103, %104, %105, %106, %107, %108, %109, %110, %111, %112, %113, %114, %115, %116, %117, %118, %119, %120, %121, %122, %123, %124, %125, %126, %127}, {%128, %129, %130, %131}, %132, 1, 1, 1, 1;\n"
    : "+f"(d[0]), "+f"(d[1]), "+f"(d[2]), "+f"(d[3]), "+f"(d[4]), "+f"(d[5]), "+f"(d[6]), "+f"(d[7]), "+f"(d[8]), "+f"(d[9]), "+f"(d[10]), "+f"(d[11]), "+f"(d[12]), "+f"(d[13]), "+f"(d[14]), "+f"(d[15]), "+f"(d[16]), "+f"(d[17]), "+f"(d[18]), "+f"(d[19]), "+f"(d[20]), "+f"(d[21]), "+f"(d[22]), "+f"(d[23]), "+f"(d[24]), "+f"(d[25]), "+f"(d[26]), "+f"(d[27]), "+f"(d[28]), "+f"(d[29]), "+f"(d[30]), "+f"(d[31]), "+f"(d[32]), "+f"(d[33]), "+f"(d[34]), "+f"(d[35]), "+f"(d[36]), "+f"(d[37]), "+f"(d[38]), "+f"(d[39]), "+f"(d[40]), "+f"(d[41]), "+f"(d[42]), "+f"(d[43]), "+f"(d[44]), "+f"(d[45]), "+f"(d[46]), "+f"(d[47]), "+f"(d[48]), "+f"(d[49]), "+f"(d[50]), "+f"(d[51]), "+f"(d[52]), "+f"(d[53]), "+f"(d[54]), "+f"(d[55]), "+f"(d[56]), "+f"(d[57]), "+f"(d[58]), "+f"(d[59]), "+f"(d[60]), "+f"(d[61]), "+f"(d[62]), "+f"(d[63]), "+f"(d[64]), "+f"(d[65]), "+f"(d[66]), "+f"(d[67]), "+f"(d[68]), "+f"(d[69]), "+f"(d[70]), "+f"(d[71]), "+f"(d[72]), "+f"(d[73]), "+f"(d[74]), "+f"(d[75]), "+f"(d[76]), "+f"(d[77]), "+f"(d[78]), "+f"(d[79]), "+f"(d[80]), "+f"(d[81]), "+f"(d[82]), "+f"(d[83]), "+f"(d[84]), "+f"(d[85]), "+f"(d[86]), "+f"(d[87]), "+f"(d[88]), "+f"(d[89]), "+f"(d[90]), "+f"(d[91]), "+f"(d[92]), "+f"(d[93]), "+f"(d[94]), "+f"(d[95]), "+f"(d[96]), "+f"(d[97]), "+f"(d[98]), "+f"(d[99]), "+f"(d[100]), "+f"(d[101]), "+f"(d[102]), "+f"(d[103]), "+f"(d[104]), "+f"(d[105]), "+f"(d[106]), "+f"(d[107]), "+f"(d[108]), "+f"(d[109]), "+f"(d[110]), "+f"(d[111]), "+f"(d[112]), "+f"(d[113]), "+f"(d[114]), "+f"(d[115]), "+f"(d[116]), "+f"(d[117]), "+f"(d[118]), "+f"(d[119]), "+f"(d[120]), "+f"(d[121]), "+f"(d[122]), "+f"(d[123]), "+f"(d[124]), "+f"(d[125]), "+f"(d[126]), "+f"(d[127])
    : "r"(a[0]), "r"(a[1]), "r"(a[2]), "r"(a[3]), "l"(db));
}

__device__ __forceinline__ uint32_t smem_u32(const void* p) { return (uint32_t)__cvta_generic_to_shared(p); }
__device__ __forceinline__ void mbar_init(uint32_t a, uint32_t cnt) { asm volatile("mbarrier.init.shared::cta.b64 [%0], %1;" ::"r"(a), "r"(cnt)); }
__device__ __forceinline__ void mbar_expect_tx(uint32_t a, uint32_t bytes) {
  asm volatile("mbarrier.arrive.expect_tx.shared::cta.b64 _, [%0], %1;" ::"r"(a), "r"(bytes) : "memory");
}
__device__ __forceinline__ void mbar_arrive_cluster(uint32_t a, uint32_t cta) {
  asm volatile("{\n.reg .b32 ra;\nmapa.shared::cluster.u32 ra, %0, %1;\nmbarrier.arrive.shared::cluster.b64 _, [ra];\n}\n" ::"r"(a), "r"(cta) : "memory");
}
__device__ __forceinline__ void mbar_arrive_both(uint32_t a) {
  mbar_arrive_cluster(a, 0); mbar_arrive_cluster(a, 1);
}
__device__ __forceinline__ void mbar_wait(uint32_t a, uint32_t parity, int code) {
  asm volatile("{\n.reg .pred p, q;\n.reg .u32 c;\nmov.u32 c, 0;\n"
               "LW:\nmbarrier.try_wait.parity.shared::cta.b64 p, [%0], %1;\n@p bra DW;\n"
               "add.u32 c, c, 1;\nsetp.lt.u32 q, c, 0x4000000;\n@q bra LW;\ntrap;\nDW:\n}\n" ::"r"(a), "r"(parity) : "memory");
}
__device__ __forceinline__ bool mbar_test(uint32_t a, uint32_t parity) {
  uint32_t ok;
  asm volatile("{\n.reg .pred p;\nmbarrier.test_wait.parity.shared::cta.b64 p, [%1], %2;\nselp.u32 %0, 1, 0, p;\n}\n" : "=r"(ok) : "r"(a), "r"(parity) : "memory");
  return __all_sync(0xffffffffu, ok != 0);
}
__device__ __forceinline__ void tma_load_2d(uint32_t dst, const CUtensorMap* map, int c0, int c1, uint32_t mbar) {
  asm volatile("cp.async.bulk.tensor.2d.shared::cluster.global.mbarrier::complete_tx::bytes [%0], [%1, {%3, %4}], [%2];" ::"r"(dst), "l"(map), "r"(mbar), "r"(c0), "r"(c1) : "memory");
}
__device__ __forceinline__ void tma_load_2d_mc(uint32_t dst, const CUtensorMap* map, int c0, int c1, uint32_t mbar, uint16_t mask) {
  asm volatile("cp.async.bulk.tensor.2d.shared::cluster.global.mbarrier::complete_tx::bytes.multicast::cluster [%0], [%1, {%3, %4}], [%2], %5;" ::"r"(dst), "l"(map), "r"(mbar), "r"(c0), "r"(c1), "h"(mask) : "memory");
}
__device__ __forceinline__ void tma_load_3d_mc(uint32_t dst, const CUtensorMap* map, int c0, int c1, int c2, uint32_t mbar, uint16_t mask) {
  asm volatile("cp.async.bulk.tensor.3d.shared::cluster.global.mbarrier::complete_tx::bytes.multicast::cluster [%0], [%1, {%3, %4, %5}], [%2], %6;" ::"r"(dst), "l"(map), "r"(mbar), "r"(c0), "r"(c1), "r"(c2), "h"(mask) : "memory");
}
__device__ __forceinline__ void tma_prefetch_3d(const CUtensorMap* map, int c0, int c1, int c2) {
  asm volatile("cp.async.bulk.prefetch.tensor.3d.L2.global.tile [%0, {%1, %2, %3}];" ::"l"(map), "r"(c0), "r"(c1), "r"(c2) : "memory");
}
__device__ __forceinline__ void wgmma_fence() { asm volatile("wgmma.fence.sync.aligned;" ::: "memory"); }
__device__ __forceinline__ void wgmma_fence_nm() { asm volatile("wgmma.fence.sync.aligned;"); }
__device__ __forceinline__ void wgmma_commit() { asm volatile("wgmma.commit_group.sync.aligned;" ::: "memory"); }
template <int N> __device__ __forceinline__ void wgmma_wait() { asm volatile("wgmma.wait_group.sync.aligned %0;" ::"n"(N) : "memory"); }
__device__ __forceinline__ uint64_t make_desc(uint32_t saddr, uint32_t lbo, uint32_t sbo) {
  return (uint64_t)((saddr & 0x3FFFF) >> 4) | ((uint64_t)(lbo >> 4) << 16) | ((uint64_t)(sbo >> 4) << 32) | (1ull << 62);
}
__device__ __forceinline__ void fence_proxy_async() { asm volatile("fence.proxy.async.global;" ::: "memory"); }
__device__ __forceinline__ void named_bar(int id, int n) { asm volatile("bar.sync %0, %1;" ::"r"(id), "r"(n) : "memory"); }
__device__ __forceinline__ void cluster_sync() {
  asm volatile("barrier.cluster.arrive.release.aligned;\nbarrier.cluster.wait.acquire.aligned;" ::: "memory");
}
__device__ __forceinline__ unsigned ld_acquire(const unsigned* p) {
  unsigned v;
  asm volatile("ld.acquire.gpu.global.u32 %0, [%1];" : "=r"(v) : "l"(p) : "memory");
  return v;
}
__device__ __forceinline__ unsigned flag_wait(const unsigned* p, unsigned target, int code) {
#pragma unroll 1
  for (uint32_t it = 0; it < SPIN_MAX; ++it) {
    unsigned v = ld_acquire(p);
    if (v >= target) return v;
    __nanosleep(20);
  }
  FAIL(code);
  return 0;
}
__device__ __forceinline__ void warp_flag_wait(const unsigned* p, unsigned target) {
#pragma unroll 1
  for (uint32_t it = 0; it < (1u << 24); ++it) {
    if (__all_sync(0xffffffffu, ld_acquire(p) >= target)) return;
    __nanosleep(20);
  }
  __trap();
}
__device__ __forceinline__ void flag_add(unsigned* p) {
  asm volatile("red.release.gpu.global.add.u32 [%0], 1;" ::"l"(p) : "memory");
}
__device__ __forceinline__ void agent_exit() {
  __threadfence();
  unsigned old = atomicAdd(&g_flags[272], 1u);
  if (old == NAGENTS - 1) {
    for (int i = 0; i < 273; ++i) g_flags[i] = 0;
    __threadfence();
  }
}
__device__ __forceinline__ float bf16r(float v) { return __bfloat162float(__float2bfloat16_rn(v)); }
__device__ __forceinline__ uint32_t pack_bf16(float lo, float hi) {
  uint32_t r;
  asm("cvt.rn.bf16x2.f32 %0, %1, %2;" : "=r"(r) : "f"(hi), "f"(lo));
  return r;
}
__device__ __forceinline__ void quad_transpose(uint32_t& v0, uint32_t& v1, uint32_t& v2, uint32_t& v3, int q) {
  bool b0 = q & 1;
  uint32_t s0 = b0 ? v0 : v1, s1 = b0 ? v2 : v3;
  s0 = __shfl_xor_sync(0xffffffffu, s0, 1);
  s1 = __shfl_xor_sync(0xffffffffu, s1, 1);
  if (b0) { v0 = s0; v2 = s1; } else { v1 = s0; v3 = s1; }
  bool b1 = q & 2;
  s0 = b1 ? v0 : v2; s1 = b1 ? v1 : v3;
  s0 = __shfl_xor_sync(0xffffffffu, s0, 2);
  s1 = __shfl_xor_sync(0xffffffffu, s1, 2);
  if (b1) { v0 = s0; v1 = s1; } else { v2 = s0; v3 = s1; }
}

struct Tile { int is_h; int col; int nb; };
__device__ __forceinline__ int num_tiles(int j) { return j ? 6 : 5; }
__device__ __forceinline__ Tile get_tile(int p, int j, int t) {
  Tile T;
  if (t == 0) {
    T.is_h = 0;
    if (j == 0) { T.col = 256 * p; T.nb = 4; }
    else { T.col = 1024 + 192 * p; T.nb = (p == 3) ? 2 : 3; }
  } else {
    T.is_h = 1; T.col = 128 * (9 * p + (j ? 4 : 0) + (t - 1)); T.nb = 4;
  }
  return T;
}

template <int NB> struct Acc { float a[NB * 32]; };
template <int NB> __device__ __forceinline__ void wgmma_nb(float (&d)[NB * 32], uint64_t da, uint64_t db, int sc);
template <> __device__ __forceinline__ void wgmma_nb<2>(float (&d)[64], uint64_t da, uint64_t db, int sc) { wgmma_n128(d, da, db, sc); }
template <> __device__ __forceinline__ void wgmma_nb<3>(float (&d)[96], uint64_t da, uint64_t db, int sc) { wgmma_n192(d, da, db, sc); }
template <> __device__ __forceinline__ void wgmma_nb<4>(float (&d)[128], uint64_t da, uint64_t db, int sc) { wgmma_n256(d, da, db, sc); }
template <int NB> __device__ __forceinline__ void wgmma_rs_nb(float (&d)[NB * 32], const uint32_t (&a)[4], uint64_t db);
template <> __device__ __forceinline__ void wgmma_rs_nb<2>(float (&d)[64], const uint32_t (&a)[4], uint64_t db) { wgmma_rs_n128(d, a, db); }
template <> __device__ __forceinline__ void wgmma_rs_nb<3>(float (&d)[96], const uint32_t (&a)[4], uint64_t db) { wgmma_rs_n192(d, a, db); }
template <> __device__ __forceinline__ void wgmma_rs_nb<4>(float (&d)[128], const uint32_t (&a)[4], uint64_t db) { wgmma_rs_n256(d, a, db); }

struct Ctx {
  uint32_t sbase;
  uint32_t full1, empty1, full2, empty2;
  uint32_t peer;
  int wg;
  int tid;
};

__device__ __forceinline__ void publish(unsigned* flag) {
  __threadfence();
  __syncwarp();
  if ((threadIdx.x & 31) == 0) flag_add(flag);
}
__device__ __forceinline__ void release2(const Ctx& c, uint32_t sa, uint32_t sb) {
  if (c.tid < 4) mbar_arrive_cluster(c.empty1 + 8 * ((c.tid & 2) ? sb : sa), c.tid & 1);
}
template <int NB>
__device__ __forceinline__ void g1_tile(const Ctx& c, float (&acc)[NB * 32], const int t  , const uint32_t (&areg)[8][4]) {
  const uint32_t abase = c.sbase + c.wg * 8192;
  wgmma_fence();
  uint32_t s = (uint32_t)(18 * t) % NS1, ph = ((uint32_t)(18 * t) / NS1) & 1, sp = 0;
#pragma unroll 1
  for (int kb = 0; kb < 14; ++kb) {
    mbar_wait(c.full1 + 8 * s, ph, 0);
    const uint32_t a0 = abase + (kb >> 1) * 16384 + (kb & 1) * 64;
    const uint32_t b0 = c.sbase + slot1_off(s);
    wgmma_nb<NB>(acc, make_desc(a0, 16, 1024), make_desc(b0, 4096, 1024), kb > 0);
    wgmma_nb<NB>(acc, make_desc(a0 + 32, 16, 1024), make_desc(b0 + 2048, 4096, 1024), 1);
    wgmma_commit();
    wgmma_wait<1>();
    if (kb > 0 && c.tid < 2) mbar_arrive_cluster(c.empty1 + 8 * sp, c.tid);
    sp = s;
    if (++s == NS1) { s = 0; ph ^= 1; }
  }
#pragma unroll
  for (int kk = 0; kk < 4; ++kk) {
    mbar_wait(c.full1 + 8 * s, ph, 0);
    const uint32_t b0 = c.sbase + slot1_off(s);
    wgmma_rs_nb<NB>(acc, areg[2 * kk], make_desc(b0, 4096, 1024));
    wgmma_rs_nb<NB>(acc, areg[2 * kk + 1], make_desc(b0 + 2048, 4096, 1024));
    wgmma_commit();
    wgmma_wait<1>();
    if (c.tid < 2) mbar_arrive_cluster(c.empty1 + 8 * sp, c.tid);
    sp = s;
    if (++s == NS1) { s = 0; ph ^= 1; }
  }
  wgmma_wait<0>();
  if (c.tid < 2) mbar_arrive_cluster(c.empty1 + 8 * sp, c.tid);
}

template <int NB>
__device__ __forceinline__ void epi_h(const Ctx& c, float (&acc)[NB * 32], int row0  , int hcol) {
  constexpr int G = NB * 4;
  const int lane = c.tid & 31, w = c.tid >> 5, q = lane & 3;
  const int r = row0 + c.wg * 64 + w * 16 + (lane >> 2);
  __nv_bfloat16* dst0 = g_act + (size_t)r * ACT_ + 576 + hcol + q * 8;
  __nv_bfloat16* dst1 = dst0 + 8 * ACT_;
  const __nv_bfloat162 zero2 = __floats2bfloat162_rn(0.f, 0.f);
#pragma unroll
  for (int a = 0; a < G / 4; ++a) {
    uint32_t v[4], u[4];
#pragma unroll
    for (int i = 0; i < 4; ++i) {
      int g = 4 * a + i;
      uint32_t g0 = pack_bf16(acc[4 * g], acc[4 * g + 1]), g1 = pack_bf16(acc[4 * g + 2], acc[4 * g + 3]);
      uint32_t u0 = pack_bf16(acc[4 * (g + G)], acc[4 * (g + G) + 1]), u1 = pack_bf16(acc[4 * (g + G) + 2], acc[4 * (g + G) + 3]);
      __nv_bfloat162 h0 = __hmul2(__hmax2(*(__nv_bfloat162*)&g0, zero2), *(__nv_bfloat162*)&u0);
      __nv_bfloat162 h1 = __hmul2(__hmax2(*(__nv_bfloat162*)&g1, zero2), *(__nv_bfloat162*)&u1);
      v[i] = *(uint32_t*)&h0; u[i] = *(uint32_t*)&h1;
    }
    quad_transpose(v[0], v[1], v[2], v[3], q);
    quad_transpose(u[0], u[1], u[2], u[3], q);
    *(uint4*)(dst0 + a * 32) = make_uint4(v[0], v[1], v[2], v[3]);
    *(uint4*)(dst1 + a * 32) = make_uint4(u[0], u[1], u[2], u[3]);
  }
}
template <int NB>
__device__ __forceinline__ void epi_qkv(const Ctx& c, float (&acc)[NB * 32], int row0, int col) {
  constexpr int G = NB * 8;
  const int lane = c.tid & 31, w = c.tid >> 5, q = lane & 3;
  const int r = row0 + c.wg * 64 + w * 16 + (lane >> 2);
  __nv_bfloat16* dst0 = g_qkv + (size_t)r * QKV_ + col + q * 8;
  __nv_bfloat16* dst1 = dst0 + 8 * QKV_;
#pragma unroll
  for (int a = 0; a < G / 4; ++a) {
    uint32_t v[4], u[4];
#pragma unroll
    for (int i = 0; i < 4; ++i) {
      int g = 4 * a + i;
      v[i] = pack_bf16(acc[4 * g], acc[4 * g + 1]); u[i] = pack_bf16(acc[4 * g + 2], acc[4 * g + 3]);
    }
    quad_transpose(v[0], v[1], v[2], v[3], q);
    quad_transpose(u[0], u[1], u[2], u[3], q);
    *(uint4*)(dst0 + a * 32) = make_uint4(v[0], v[1], v[2], v[3]);
    *(uint4*)(dst1 + a * 32) = make_uint4(u[0], u[1], u[2], u[3]);
  }
}
__device__ __forceinline__ void mbar_arrive_local(uint32_t a) { asm volatile("mbarrier.arrive.shared::cta.b64 _, [%0];" ::"r"(a) : "memory"); }

template <int NA>
__device__ __forceinline__ void acc_to_smem(float (&acc)[NA], uint32_t a0  , uint32_t pitch) {
#pragma unroll
  for (int g = 0; g < NA / 4; ++g) {
    asm volatile("st.shared.v2.f32 [%0], {%1, %2};" ::"r"(a0 + g * 32), "f"(acc[4 * g]), "f"(acc[4 * g + 1]) : "memory");
    asm volatile("st.shared.v2.f32 [%0], {%1, %2};" ::"r"(a0 + 8 * pitch + g * 32), "f"(acc[4 * g + 2]), "f"(acc[4 * g + 3]) : "memory");
  }
}
__device__ __forceinline__ float4 lds128(uint32_t a) {
  float4 v;
  asm volatile("ld.shared.v4.f32 {%0, %1, %2, %3}, [%4];" : "=f"(v.x), "=f"(v.y), "=f"(v.z), "=f"(v.w) : "r"(a));
  return v;
}

__device__ __forceinline__ void mma16816(float (&c)[4], uint32_t a0, uint32_t a1, uint32_t a2, uint32_t a3, uint32_t b0, uint32_t b1) {
  asm volatile("mma.sync.aligned.m16n8k16.row.col.f32.bf16.bf16.f32 {%0,%1,%2,%3}, {%4,%5,%6,%7}, {%8,%9}, {%0,%1,%2,%3};"
               : "+f"(c[0]), "+f"(c[1]), "+f"(c[2]), "+f"(c[3]) : "r"(a0), "r"(a1), "r"(a2), "r"(a3), "r"(b0), "r"(b1));
}
__device__ __forceinline__ uint32_t movm(uint32_t a) {
  uint32_t d;
  asm volatile("movmatrix.sync.aligned.m8n8.trans.b16 %0, %1;" : "=r"(d) : "r"(a));
  return d;
}
struct HeadRegs { uint32_t q[2][3], k[4][3], v[4][3]; };
__device__ __forceinline__ void load_head(HeadRegs& R, int h, int qrow, int g, int t) {
  const int o = h & 1;
  const int wp = 9 * h + o + 2 * t, wt = 9 * h + (o ? 0 : 8);
#pragma unroll
  for (int r = 0; r < 2; ++r) {
    const uint32_t* p = (const uint32_t*)(g_qkv + (size_t)(qrow + g + 8 * r) * QKV_);
    uint2 a = *(const uint2*)(p + wp);
    R.q[r][0] = a.x; R.q[r][1] = a.y; R.q[r][2] = t == 0 ? p[wt] : 0u;
  }
#pragma unroll
  for (int nt = 0; nt < 4; ++nt) {
    const int jj = 8 * nt + g, kr = qrow - 14 + jj;
    const bool ok = (kr >= 0) && (jj < 30);
    const uint32_t* p = (const uint32_t*)(g_qkv + (size_t)(ok ? kr : qrow) * QKV_);
    uint2 a = make_uint2(0u, 0u);
    if (ok) a = *(const uint2*)(p + 288 + wp);
    R.k[nt][0] = a.x; R.k[nt][1] = a.y; R.k[nt][2] = (ok && t == 0) ? p[288 + wt] : 0u;
    R.v[nt][0] = ok ? p[576 + 9 * h + t] : 0u; R.v[nt][1] = ok ? p[576 + 9 * h + 4 + t] : 0u;
    R.v[nt][2] = (ok && t == 0) ? p[576 + 9 * h + 8] : 0u;
  }
}
__device__ __noinline__ void attention(int row0, int role, int m, int aw, int lane) {
  warp_flag_wait(&g_flags[((lane >= 8 && role == 0 && m > 0) ? m - 1 : m) * 8 + (lane & 7)], 1);
  if (aw == 0 && lane == 0) TS2(24);
  const float scale = 0.23570226039551584f;
  const int g = lane >> 2, t = lane & 3;
  const int qrow = row0 + role * 16;
  HeadRegs N;
  load_head(N, aw, qrow, g, t);
#pragma unroll 1
  for (int h = aw; h < 32; h += 8) {
    HeadRegs R = N;
    if (h + 8 < 32) load_head(N, h + 8, qrow, g, t);
    float sc[4][4];
#pragma unroll
    for (int nt = 0; nt < 4; ++nt) {
      sc[nt][0] = sc[nt][1] = sc[nt][2] = sc[nt][3] = 0.f;
      mma16816(sc[nt], R.q[0][0], R.q[1][0], R.q[0][1], R.q[1][1], R.k[nt][0], R.k[nt][1]);
      mma16816(sc[nt], R.q[0][2], R.q[1][2], 0u, 0u, R.k[nt][2], 0u);
    }
    const int par = g & 1;
    float l0[4], l1[4];
    float mx0 = -3.0e38f, mx1 = -3.0e38f;
#pragma unroll
    for (int nt = 0; nt < 4; ++nt) {
      const int jj = 8 * nt + 2 * t + par;
      const int d0 = g + 14 - jj, d1 = d0 + 8;
      const bool inr = qrow - 14 + jj >= 0;
      const bool ok0 = inr && d0 >= 0 && d0 <= 14, ok1 = inr && d1 >= 0 && d1 <= 14;
      uint32_t pk = pack_bf16(par ? sc[nt][1] : sc[nt][0], par ? sc[nt][3] : sc[nt][2]);
      pk = pack_bf16(__uint_as_float(pk << 16) * scale, __uint_as_float(pk & 0xffff0000u) * scale);
      l0[nt] = ok0 ? __uint_as_float(pk << 16) : -3.0e38f;
      l1[nt] = ok1 ? __uint_as_float(pk & 0xffff0000u) : -3.0e38f;
      mx0 = fmaxf(mx0, l0[nt]); mx1 = fmaxf(mx1, l1[nt]);
    }
    mx0 = fmaxf(mx0, __shfl_xor_sync(0xffffffffu, mx0, 1)); mx0 = fmaxf(mx0, __shfl_xor_sync(0xffffffffu, mx0, 2));
    mx1 = fmaxf(mx1, __shfl_xor_sync(0xffffffffu, mx1, 1)); mx1 = fmaxf(mx1, __shfl_xor_sync(0xffffffffu, mx1, 2));
    float s0 = 0.f, s1 = 0.f;
#pragma unroll
    for (int nt = 0; nt < 4; ++nt) {
      l0[nt] = __expf(l0[nt] - mx0); l1[nt] = __expf(l1[nt] - mx1);
      s0 += l0[nt]; s1 += l1[nt];
    }
    s0 += __shfl_xor_sync(0xffffffffu, s0, 1); s0 += __shfl_xor_sync(0xffffffffu, s0, 2);
    s1 += __shfl_xor_sync(0xffffffffu, s1, 1); s1 += __shfl_xor_sync(0xffffffffu, s1, 2);
    const float i0 = __frcp_rn(s0), i1 = __frcp_rn(s1);
    uint32_t pa[2][4];
#pragma unroll
    for (int nt = 0; nt < 4; ++nt) {
      const float p0 = l0[nt] * i0, p1 = l1[nt] * i1;
      pa[nt >> 1][(nt & 1) * 2] = par ? pack_bf16(0.f, p0) : pack_bf16(p0, 0.f);
      pa[nt >> 1][(nt & 1) * 2 + 1] = par ? pack_bf16(0.f, p1) : pack_bf16(p1, 0.f);
    }
    uint32_t* o0p = (uint32_t*)(g_act + (size_t)(qrow + g) * ACT_) + 9 * h;
    uint32_t* o1p = (uint32_t*)(g_act + (size_t)(qrow + g + 8) * ACT_) + 9 * h;
#pragma unroll
    for (int cg = 0; cg < 3; ++cg) {
      float oc[4] = {0.f, 0.f, 0.f, 0.f};
      mma16816(oc, pa[0][0], pa[0][1], pa[0][2], pa[0][3], movm(R.v[0][cg]), movm(R.v[1][cg]));
      mma16816(oc, pa[1][0], pa[1][1], pa[1][2], pa[1][3], movm(R.v[2][cg]), movm(R.v[3][cg]));
      if (cg < 2 || t == 0) {
        o0p[4 * cg + t] = pack_bf16(oc[0], oc[1]);
        o1p[4 * cg + t] = pack_bf16(oc[2], oc[3]);
      }
    }
  }
  if (aw == 0 && lane == 0) TS2(26);
}

__global__ void __cluster_dims__(2, 1, 1) __launch_bounds__(384, 1)
fused_kernel(const __grid_constant__ CUtensorMap m_qkv1, const __grid_constant__ CUtensorMap m_qkv2,
             const __grid_constant__ CUtensorMap m_gate2, const __grid_constant__ CUtensorMap m_up2,
             const __grid_constant__ CUtensorMap m_wo5, const __grid_constant__ CUtensorMap m_wo4,
             const __grid_constant__ CUtensorMap m_down5, const __grid_constant__ CUtensorMap m_down4,
             const __grid_constant__ CUtensorMap m_act,
             const __nv_bfloat16* __restrict__ x, __nv_bfloat16* __restrict__ out) {
  extern __shared__ uint8_t smem_raw[];
  const uint32_t sbase = (smem_u32(smem_raw) + 1023) & ~1023u;
  const uint32_t bars = sbase + DATA_BYTES;
  const uint32_t full1 = bars, empty1 = bars + 64, full2 = bars + 128, empty2 = bars + 192, pub = bars + 256;
  const int rank = blockIdx.x & 1, cl = blockIdx.x >> 1;
  const int role = cl & 7, m = (cl >> 3) * 2 + rank, p = role >> 1, j = role & 1;
  const int row0 = m * 128;
  const int warp = __shfl_sync(0xffffffffu, (int)(threadIdx.x >> 5), 0), lane = threadIdx.x & 31;
  const int nkb2 = (p == 3) ? 21 : 20;
  const int nblk2 = j ? 4 : 5;
  const int ncol0 = j ? 320 : 0;

  uint4 nx[9];
  if (warp >= 4) {
    const int cw = warp - 4;
    const uint4* src = (const uint4*)(x + (size_t)(row0 + cw * 16 + (lane >> 3)) * D_) + (lane & 7);
#pragma unroll
    for (int t = 0; t < 9; ++t) nx[t] = __ldg(src + 8 * t);
  }
  if (threadIdx.x == 0) {
    for (int s = 0; s < NS1; ++s) { mbar_init(full1 + 8 * s, 1); mbar_init(empty1 + 8 * s, MC ? 4 : 2); }
    for (int s = 0; s < NS2; ++s) { mbar_init(full2 + 8 * s, 1); mbar_init(empty2 + 8 * s, MC ? 4 : 2); }
    for (int s = 0; s < 7; ++s) mbar_init(pub + 8 * s, 256);
    asm volatile("fence.mbarrier_init.release.cluster;" ::: "memory");
  }
  __syncthreads();
  cluster_sync();

  if (warp < 4) {
    asm volatile("setmaxnreg.dec.sync.aligned.u32 40;");
    if (warp == 0) {
      if (lane == 0) {
        uint32_t it = 0;
        const int nt = num_tiles(j);
        volatile uint32_t* known = (volatile uint32_t*)(smem_raw + (bars + 320 - smem_u32(smem_raw)));
        volatile uint32_t* sched = known + 12;
        for (int t = 0; t < nt; ++t) {
          Tile T = get_tile(p, j, t);
          const CUtensorMap* mp; int cb, nmine;
          if (T.is_h) { mp = rank ? &m_up2 : &m_gate2; cb = T.col >> 6; nmine = 2; }
          else if (T.nb == 4) { mp = &m_qkv2; cb = (T.col >> 6) + 2 * rank; nmine = 2; }
          else if (T.nb == 3) { mp = rank ? &m_qkv1 : &m_qkv2; cb = (T.col >> 6) + 2 * rank; nmine = rank ? 1 : 2; }
          else { mp = &m_qkv1; cb = (T.col >> 6) + rank; nmine = 1; }
          const uint32_t doff = (T.nb == 2 ? rank : 2 * rank) * 4096;
          for (int kb = 0; kb < 18; ++kb, ++it) {
            uint32_t s = it % NS1, ph = (it / NS1) & 1;
            if (it == 5) {
              for (int r = 0; r < 9; ++r) known[r] = 0;
              const int hlo = p == 0 ? 0 : 20 * p - 9, hhi = 20 * p + 11 + (p == 3 ? 1 : 0);
              int n = 0;
              for (int tt = 1; tt <= 5; ++tt)
                for (int hb = hlo; hb < hhi; ++hb) {
                  int TT = hb >> 1, pp = TT / 9, idx = TT - 9 * pp;
                  int ot = 1 + (idx >= 4 ? idx - 4 : idx);
                  if (ot == tt) sched[n++] = (uint32_t)hb | ((uint32_t)(2 * pp + (idx >= 4)) << 8) | ((uint32_t)(ot + 1) << 16);
                }
            }
            mbar_wait(empty1 + 8 * s, s >= 5 ? ph : ph ^ 1, 1);
            mbar_expect_tx(full1 + 8 * s, T.nb * 4096);
            tma_load_3d_mc(sbase + slot1_off(s) + doff, mp, 0, kb * 32, cb, full1 + 8 * s, 3);
            (void)nmine;
          }
        }
        const CUtensorMap* mwo = j ? &m_wo4 : &m_wo5;
        const CUtensorMap* mdn = j ? &m_down4 : &m_down5;
        for (int i = 0; i < nkb2; ++i) {
          uint32_t s = i % NS2, ph = (i / NS2) & 1;
          int acol, kn, wrow; const CUtensorMap* mp; const unsigned* fl; unsigned tgt;
          if (p == 0 && i >= 11) {
            acol = (i - 11) * 64; mp = mwo; wrow = acol; fl = &g_flags[128 + m]; tgt = 8; kn = 8;
          } else {
            uint32_t e = sched[i];
            wrow = (e & 255) * 64; kn = (e >> 8) & 255; tgt = e >> 16;
            acol = 576 + wrow; mp = mdn; fl = &g_flags[m * 8 + kn];
          }
          mbar_wait(empty2 + 8 * s, ph, 2);
          mbar_expect_tx(full2 + 8 * s, 16384 + nblk2 * 8192);
          uint32_t dst = sbase + s * ST2_BYTES;
          tma_load_3d_mc(dst + 16384 + rank * nblk2 * 4096, mp, 0, wrow + 32 * rank, ncol0 >> 6, full2 + 8 * s, 3);
          if (known[kn] < tgt) { known[kn] = flag_wait(fl, tgt, 4); fence_proxy_async(); }
          tma_load_2d(dst, &m_act, acol, row0, full2 + 8 * s);
          TS2(32 + i);
        }
        agent_exit();
      }
    } else if (warp == 1) {
      const int nt = num_tiles(j);
      for (int t = 0; t < nt; ++t) {
        mbar_wait(pub + 8 * t, 0, 7);
        if (lane == 0) { if (t == 0) TS2(27); __threadfence(); flag_add(&g_flags[m * 8 + role]); if (t == 0) TS2(28); }
        __syncwarp();
        if (t == 1) {
          mbar_wait(pub + 8 * 6, 0, 7);
          if (lane == 0) { __threadfence(); flag_add(&g_flags[128 + m]); }
          __syncwarp();
        }
      }
      if (lane == 0) agent_exit();
    } else if (warp == 2) {
      if (lane == 0) {
        const int mp8 = cl >> 3, nt = num_tiles(j);
        for (int t = 1; t <= nt; ++t) {
          if (t >= 2) mbar_wait(pub + 8 * (t - 2), 0, 7);
          if (t < nt) {
            Tile T = get_tile(p, j, t);
            for (int kb = mp8; kb < 18; kb += 8) tma_prefetch_3d(rank ? &m_up2 : &m_gate2, 0, kb * 32, T.col >> 6);
          } else {
            const int hlo = p == 0 ? 0 : 20 * p - 9, hhi = 20 * p + 11 + (p == 3 ? 1 : 0);
            for (int hb = hlo + mp8; hb < hhi; hb += 8) tma_prefetch_3d(j ? &m_down4 : &m_down5, 0, hb * 64 + 32 * rank, ncol0 >> 6);
            if (p == 0) for (int ob = mp8; ob < 9; ob += 8) tma_prefetch_3d(j ? &m_wo4 : &m_wo5, 0, ob * 64 + 32 * rank, ncol0 >> 6);
          }
        }
      }
    }
  } else {
    asm volatile("setmaxnreg.inc.sync.aligned.u32 232;");
    Ctx c;
    c.sbase = sbase; c.full1 = full1; c.empty1 = empty1; c.full2 = full2; c.empty2 = empty2; c.peer = rank ^ 1;
    c.wg = (warp - 4) >> 2; c.tid = threadIdx.x - 128 - c.wg * 128;
    const int w = c.tid >> 5;
    if (c.wg == 0 && c.tid == 0) TS(0);
    uint32_t areg[8][4];
    {
      const int sub = lane >> 3, li = lane & 7;
#pragma unroll 1
      for (int itr = 0; itr < 4; ++itr) {
        const int r = c.wg * 64 + w * 16 + itr * 4 + sub;
        uint4 xv[9];
#pragma unroll
        for (int t = 0; t < 9; ++t) xv[t] = nx[t];
        if (itr < 3) {
          const uint4* src = (const uint4*)(x + (size_t)(row0 + r + 4) * D_) + li;
#pragma unroll
          for (int t = 0; t < 9; ++t) nx[t] = __ldg(src + 8 * t);
        }
        float s0 = 0.f, s1 = 0.f;
#pragma unroll
        for (int t = 0; t < 9; ++t) {
          const uint32_t* u = (const uint32_t*)&xv[t];
#pragma unroll
          for (int e = 0; e < 4; ++e) { s0 += __uint_as_float(u[e] << 16); s1 += __uint_as_float(u[e] & 0xffff0000u); }
        }
        float sum = s0 + s1;
        sum += __shfl_xor_sync(0xffffffffu, sum, 1); sum += __shfl_xor_sync(0xffffffffu, sum, 2); sum += __shfl_xor_sync(0xffffffffu, sum, 4);
        const float mean = sum * (1.f / 576.f);
        float q0 = 0.f, q1 = 0.f;
#pragma unroll
        for (int t = 0; t < 9; ++t) {
          const uint32_t* u = (const uint32_t*)&xv[t];
#pragma unroll
          for (int e = 0; e < 4; ++e) {
            float a = __uint_as_float(u[e] << 16) - mean, b = __uint_as_float(u[e] & 0xffff0000u) - mean;
            q0 = fmaf(a, a, q0); q1 = fmaf(b, b, q1);
          }
        }
        float sq = q0 + q1;
        sq += __shfl_xor_sync(0xffffffffu, sq, 1); sq += __shfl_xor_sync(0xffffffffu, sq, 2); sq += __shfl_xor_sync(0xffffffffu, sq, 4);
        const float vb = bf16r(sq * (1.f / 576.f));
        const float rinv = 1.f / bf16r(sqrtf(bf16r(vb + 1e-5f)));
        const __nv_bfloat162 mb2 = __float2bfloat162_rn(mean);
        const uint32_t dsta = sbase + r * 128 + ((li ^ (r & 7)) << 4);
#pragma unroll
        for (int t = 0; t < 9; ++t) {
          const uint32_t* u = (const uint32_t*)&xv[t];
          uint32_t o[4];
#pragma unroll
          for (int e = 0; e < 4; ++e) {
            __nv_bfloat162 d2 = __hsub2(*(const __nv_bfloat162*)&u[e], mb2);
            uint32_t du = *(uint32_t*)&d2;
            o[e] = pack_bf16(__uint_as_float(du << 16) * rinv, __uint_as_float(du & 0xffff0000u) * rinv);
          }
          asm volatile("st.shared.v4.b32 [%0], {%1, %2, %3, %4};" ::"r"(dsta + t * 16384), "r"(o[0]), "r"(o[1]), "r"(o[2]), "r"(o[3]) : "memory");
        }
      }
      asm volatile("fence.proxy.async.shared::cta;" ::: "memory");
      __syncwarp();
      {
        const int r = c.wg * 64 + w * 16 + (lane & 7) + ((lane >> 3) & 1) * 8;
        const int hi = lane >> 4;
#pragma unroll
        for (int ks = 0; ks < 8; ++ks) {
          const uint32_t ad = sbase + (7 + (ks >> 2)) * 16384 + r * 128 + ((((ks & 3) * 2 + hi) ^ (r & 7)) << 4);
          asm volatile("ldmatrix.sync.aligned.m8n8.x4.shared.b16 {%0, %1, %2, %3}, [%4];"
                       : "=r"(areg[ks][0]), "=r"(areg[ks][1]), "=r"(areg[ks][2]), "=r"(areg[ks][3]) : "r"(ad) : "memory");
        }
      }
      named_bar(1 + c.wg, 128);
      if (c.tid == 0) { mbar_arrive_both(empty1 + 8 * 5); mbar_arrive_both(empty1 + 8 * 6); }
    }
    if (c.wg == 0 && c.tid == 0) TS(1);
    unsigned* myflag = &g_flags[m * 8 + role];
    {
      uint32_t it = 0;
      const int nt = num_tiles(j);
#pragma unroll 1
      for (int t = 0; t < nt; ++t) {
        Tile T = get_tile(p, j, t);
        if (T.nb == 4) {
          float acc[128] = {};
          g1_tile<4>(c, acc, t, areg);
          if (T.is_h) epi_h<4>(c, acc, row0, T.col); else epi_qkv<4>(c, acc, row0, T.col);
        } else if (T.nb == 3) {
          float acc[96] = {};
          g1_tile<3>(c, acc, t, areg);
          epi_qkv<3>(c, acc, row0, T.col);
        } else {
          float acc[64] = {};
          g1_tile<2>(c, acc, t, areg);
          epi_qkv<2>(c, acc, row0, T.col);
        }
        if (t == nt - 1 && c.tid == 0) {
          for (int s = 0; s < NS2; ++s) { mbar_arrive_both(empty2 + 8 * s); }
        }
        mbar_arrive_local(pub + 8 * t);
        if (t == 1) {
          if (c.wg == 0 && c.tid == 0) TS(11);
          attention(row0, role, m, c.wg * 4 + w, lane);
          mbar_arrive_local(pub + 8 * 6);
          if (c.wg == 0 && c.tid == 0) TS(12);
        }
        if (c.wg == 0 && c.tid == 0) TS(2 + t);
      }
    }
    const int nch = j ? 32 : 40;
    const uint32_t pitch = nch * 32 + 32;
    const uint32_t sacc = sbase + (c.wg * 64 + w * 16 + (lane >> 2)) * pitch + (lane & 3) * 8;
    if (j == 0) {
      float acc1[96] = {}, acc2[64] = {};
      wgmma_fence();
#pragma unroll 1
      for (int i = 0; i < nkb2; ++i) {
        uint32_t s = i % NS2, ph = (i / NS2) & 1;
        mbar_wait(full2 + 8 * s, ph, 3);
        if (c.wg == 0 && c.tid == 0) TS2(i);
        uint32_t a0 = sbase + s * ST2_BYTES + c.wg * 8192, b0 = sbase + s * ST2_BYTES + 16384;
        wgmma_fence();
#pragma unroll
        for (int k = 0; k < 4; ++k) {
          uint64_t da = make_desc(a0 + k * 32, 16, 1024);
          const uint32_t bk = b0 + (k >> 1) * (5 * 4096) + (k & 1) * 2048;
          wgmma_n192(acc1, da, make_desc(bk, 4096, 1024), (i | k) != 0);
          wgmma_n128(acc2, da, make_desc(bk + 3 * 4096, 4096, 1024), (i | k) != 0);
        }
        wgmma_commit();
        if (i > 0) {
          wgmma_wait<1>();
          if (c.tid < 2 && i - 1 + NS2 < nkb2) mbar_arrive_cluster(empty2 + 8 * ((i - 1) % NS2), c.tid);
        }
      }
      wgmma_wait<0>();
      if (c.wg == 0 && c.tid == 0) TS(8);
      named_bar(3, 256);
      acc_to_smem<96>(acc1, sacc, pitch);
      acc_to_smem<64>(acc2, sacc + 768, pitch);
    } else {
      float acc[128] = {};
      wgmma_fence();
#pragma unroll 1
      for (int i = 0; i < nkb2; ++i) {
        uint32_t s = i % NS2, ph = (i / NS2) & 1;
        mbar_wait(full2 + 8 * s, ph, 3);
        if (c.wg == 0 && c.tid == 0) TS2(i);
        uint32_t a0 = sbase + s * ST2_BYTES + c.wg * 8192, b0 = sbase + s * ST2_BYTES + 16384;
        wgmma_fence();
#pragma unroll
        for (int k = 0; k < 4; ++k)
          wgmma_n256(acc, make_desc(a0 + k * 32, 16, 1024), make_desc(b0 + (k >> 1) * (4 * 4096) + (k & 1) * 2048, 4096, 1024), (i | k) != 0);
        wgmma_commit();
        if (i > 0) {
          wgmma_wait<1>();
          if (c.tid < 2 && i - 1 + NS2 < nkb2) mbar_arrive_cluster(empty2 + 8 * ((i - 1) % NS2), c.tid);
        }
      }
      wgmma_wait<0>();
      if (c.wg == 0 && c.tid == 0) TS(8);
      named_bar(3, 256);
      acc_to_smem<128>(acc, sacc, pitch);
    }
    named_bar(3, 256);
    if (c.wg == 0 && c.tid == 0) TS2(60);
    {
      const int t256 = c.wg * 128 + c.tid;
      __nv_bfloat16* dst = g_part + ((size_t)p * S_ + row0) * D_ + ncol0;
#pragma unroll 4
      for (int e = t256; e < 128 * nch; e += 256) {
        int r = e / nch, cI = e - r * nch;
        float4 u0 = lds128(sbase + r * pitch + cI * 32), u1 = lds128(sbase + r * pitch + cI * 32 + 16);
        *(uint4*)(dst + (size_t)r * D_ + cI * 8) = make_uint4(pack_bf16(u0.x, u0.y), pack_bf16(u0.z, u0.w), pack_bf16(u1.x, u1.y), pack_bf16(u1.z, u1.w));
      }
      if (c.wg == 0 && c.tid == 0) TS(10);
    }
    named_bar(1 + c.wg, 128);
    if (c.tid == 0) agent_exit();
  }
}

__global__ void __launch_bounds__(256) reduce_kernel(const __nv_bfloat16* __restrict__ x, __nv_bfloat16* __restrict__ out) {
  const size_t i = (size_t)blockIdx.x * 256 + threadIdx.x;
  const uint4* pp = (const uint4*)g_part;
  const uint4 a = pp[i], b = pp[i + S_ * D_ / 8], c = pp[i + 2 * (S_ * D_ / 8)], d = pp[i + 3 * (S_ * D_ / 8)], xv = ((const uint4*)x)[i];
  uint32_t o[4];
#pragma unroll
  for (int e = 0; e < 4; ++e) {
    const uint32_t w0 = ((const uint32_t*)&a)[e], w1 = ((const uint32_t*)&b)[e], w2 = ((const uint32_t*)&c)[e], w3 = ((const uint32_t*)&d)[e], w4 = ((const uint32_t*)&xv)[e];
    float lo = ((__uint_as_float(w0 << 16) + __uint_as_float(w1 << 16)) + (__uint_as_float(w2 << 16) + __uint_as_float(w3 << 16))) + __uint_as_float(w4 << 16);
    float hi = ((__uint_as_float(w0 & 0xffff0000u) + __uint_as_float(w1 & 0xffff0000u)) + (__uint_as_float(w2 & 0xffff0000u) + __uint_as_float(w3 & 0xffff0000u))) + __uint_as_float(w4 & 0xffff0000u);
    o[e] = pack_bf16(lo, hi);
  }
  ((uint4*)out)[i] = make_uint4(o[0], o[1], o[2], o[3]);
}

typedef CUresult (*EncodeFn)(CUtensorMap*, CUtensorMapDataType, cuuint32_t, void*, const cuuint64_t*, const cuuint64_t*,
                             const cuuint32_t*, const cuuint32_t*, CUtensorMapInterleave, CUtensorMapSwizzle,
                             CUtensorMapL2promotion, CUtensorMapFloatOOBfill);

static void make_map2(EncodeFn enc, CUtensorMap* mp, const void* ptr, int rows, int cols, int box_rows) {
  cuuint64_t dims[2] = {(cuuint64_t)cols, (cuuint64_t)rows};
  cuuint64_t strides[1] = {(cuuint64_t)cols * 2};
  cuuint32_t box[2] = {64, (cuuint32_t)box_rows};
  cuuint32_t es[2] = {1, 1};
  enc(mp, CU_TENSOR_MAP_DATA_TYPE_BFLOAT16, 2, (void*)ptr, dims, strides, box, es, CU_TENSOR_MAP_INTERLEAVE_NONE,
      CU_TENSOR_MAP_SWIZZLE_128B, CU_TENSOR_MAP_L2_PROMOTION_L2_256B, CU_TENSOR_MAP_FLOAT_OOB_FILL_NONE);
}
static void make_map3(EncodeFn enc, CUtensorMap* mp, const void* ptr, int rows, int cols, int nblk) {
  cuuint64_t dims[3] = {64, (cuuint64_t)rows, (cuuint64_t)(cols / 64)};
  cuuint64_t strides[2] = {(cuuint64_t)cols * 2, 128};
  cuuint32_t box[3] = {64, 32, (cuuint32_t)nblk};
  cuuint32_t es[3] = {1, 1, 1};
  enc(mp, CU_TENSOR_MAP_DATA_TYPE_BFLOAT16, 3, (void*)ptr, dims, strides, box, es, CU_TENSOR_MAP_INTERLEAVE_NONE,
      CU_TENSOR_MAP_SWIZZLE_128B, CU_TENSOR_MAP_L2_PROMOTION_L2_256B, CU_TENSOR_MAP_FLOAT_OOB_FILL_NONE);
}

extern "C" void kernel_launch(void* const* d_in, const int* in_sizes, int n_in, void* d_out, int out_size) {
  static EncodeFn enc = nullptr;
  static void* act_ptr = nullptr;
  if (!enc) {
    void* fn = nullptr;
    cudaDriverEntryPointQueryResult qr;
    cudaGetDriverEntryPoint("cuTensorMapEncodeTiled", &fn, cudaEnableDefault, &qr);
    enc = (EncodeFn)fn;
    cudaGetSymbolAddress(&act_ptr, g_act);
    cudaFuncSetAttribute(fused_kernel, cudaFuncAttributeMaxDynamicSharedMemorySize, SMEM_BYTES);
  }
  const __nv_bfloat16* x = (const __nv_bfloat16*)d_in[0];
  CUtensorMap m_qkv1, m_qkv2, m_gate2, m_up2, m_wo5, m_wo4, m_down5, m_down4, m_act;
  make_map3(enc, &m_qkv1, d_in[1], D_, QKV_, 1);
  make_map3(enc, &m_qkv2, d_in[1], D_, QKV_, 2);
  make_map3(enc, &m_gate2, d_in[4], D_, F_, 2);
  make_map3(enc, &m_up2, d_in[5], D_, F_, 2);
  make_map3(enc, &m_wo5, d_in[2], D_, D_, 5);
  make_map3(enc, &m_wo4, d_in[2], D_, D_, 4);
  make_map3(enc, &m_down5, d_in[6], F_, D_, 5);
  make_map3(enc, &m_down4, d_in[6], F_, D_, 4);
  make_map2(enc, &m_act, act_ptr, S_, ACT_, 128);
  fused_kernel<<<128, 384, SMEM_BYTES>>>(m_qkv1, m_qkv2, m_gate2, m_up2, m_wo5, m_wo4, m_down5, m_down4, m_act, x, (__nv_bfloat16*)d_out);
  reduce_kernel<<<S_ * D_ / 8 / 256, 256>>>(x, (__nv_bfloat16*)d_out);
}
```

```cpp
#include <cuda_runtime.h>
#include <cuda_bf16.h>
#include <cuda.h>
#include <stdint.h>

constexpr int S_ = 2048, D_ = 576, F_ = 4608, QKV_ = 1728, ACT_ = 5184;
constexpr int NS1 = 7;
constexpr int NS2 = 4;
constexpr int XN_BYTES = 9 * 16384;
constexpr int RING1_OFF = 7 * 16384;
__device__ __forceinline__ uint32_t slot1_off(uint32_t s) { return RING1_OFF + (s >= 5 ? s - 5 : s + 2) * 16384; }
constexpr int ST1_BYTES = 16384;
constexpr int ST2_BYTES = 57344;
constexpr int DATA_BYTES = 229376;
constexpr int SMEM_BYTES = DATA_BYTES + 1024 + 512;
constexpr int NAGENTS = 128 * 4;
#define SKEW 0
#define MC 1

__device__ __align__(1024) __nv_bfloat16 g_qkv[S_ * QKV_];
__device__ __align__(1024) __nv_bfloat16 g_act[S_ * ACT_];
__device__ __align__(1024) uint4 g_xch[16 * 2 * 4 * 128 * 40];
__device__ unsigned int g_flags[288];
#define TS(i)
#define TS2(i)
#define FAIL(code) __trap()
#define SPIN_MAX (1u << 24)

__device__ __forceinline__ void wgmma_n128(float (&d)[64], uint64_t da, uint64_t db, int scale_d) {
  asm volatile("{\n.reg .pred p;\nsetp.ne.b32 p, %66, 0;\n"
    "wgmma.mma_async.sync.aligned.m64n128k16.f32.bf16.bf16 {%0, %1, %2, %3, %4, %5, %6, %7, %8, %9, %10, %11, %12, %13, %14, %15, %16, %17, %18, %19, %20, %21, %22, %23, %24, %25, %26, %27, %28, %29, %30, %31, %32, %33, %34, %35, %36, %37, %38, %39, %40, %41, %42, %43, %44, %45, %46, %47, %48, %49, %50, %51, %52, %53, %54, %55, %56, %57, %58, %59, %60, %61, %62, %63}, %64, %65, p, 1, 1, 0, 1;\n}\n"
    : "+f"(d[0]), "+f"(d[1]), "+f"(d[2]), "+f"(d[3]), "+f"(d[4]), "+f"(d[5]), "+f"(d[6]), "+f"(d[7]), "+f"(d[8]), "+f"(d[9]), "+f"(d[10]), "+f"(d[11]), "+f"(d[12]), "+f"(d[13]), "+f"(d[14]), "+f"(d[15]), "+f"(d[16]), "+f"(d[17]), "+f"(d[18]), "+f"(d[19]), "+f"(d[20]), "+f"(d[21]), "+f"(d[22]), "+f"(d[23]), "+f"(d[24]), "+f"(d[25]), "+f"(d[26]), "+f"(d[27]), "+f"(d[28]), "+f"(d[29]), "+f"(d[30]), "+f"(d[31]), "+f"(d[32]), "+f"(d[33]), "+f"(d[34]), "+f"(d[35]), "+f"(d[36]), "+f"(d[37]), "+f"(d[38]), "+f"(d[39]), "+f"(d[40]), "+f"(d[41]), "+f"(d[42]), "+f"(d[43]), "+f"(d[44]), "+f"(d[45]), "+f"(d[46]), "+f"(d[47]), "+f"(d[48]), "+f"(d[49]), "+f"(d[50]), "+f"(d[51]), "+f"(d[52]), "+f"(d[53]), "+f"(d[54]), "+f"(d[55]), "+f"(d[56]), "+f"(d[57]), "+f"(d[58]), "+f"(d[59]), "+f"(d[60]), "+f"(d[61]), "+f"(d[62]), "+f"(d[63])
    : "l"(da), "l"(db), "r"(scale_d));
}

__device__ __forceinline__ void wgmma_n192(float (&d)[96], uint64_t da, uint64_t db, int scale_d) {
  asm volatile("{\n.reg .pred p;\nsetp.ne.b32 p, %98, 0;\n"
    "wgmma.mma_async.sync.aligned.m64n192k16.f32.bf16.bf16 {%0, %1, %2, %3, %4, %5, %6, %7, %8, %9, %10, %11, %12, %13, %14, %15, %16, %17, %18, %19, %20, %21, %22, %23, %24, %25, %26, %27, %28, %29, %30, %31, %32, %33, %34, %35, %36, %37, %38, %39, %40, %41, %42, %43, %44, %45, %46, %47, %48, %49, %50, %51, %52, %53, %54, %55, %56, %57, %58, %59, %60, %61, %62, %63, %64, %65, %66, %67, %68, %69, %70, %71, %72, %73, %74, %75, %76, %77, %78, %79, %80, %81, %82, %83, %84, %85, %86, %87, %88, %89, %90, %91, %92, %93, %94, %95}, %96, %97, p, 1, 1, 0, 1;\n}\n"
    : "+f"(d[0]), "+f"(d[1]), "+f"(d[2]), "+f"(d[3]), "+f"(d[4]), "+f"(d[5]), "+f"(d[6]), "+f"(d[7]), "+f"(d[8]), "+f"(d[9]), "+f"(d[10]), "+f"(d[11]), "+f"(d[12]), "+f"(d[13]), "+f"(d[14]), "+f"(d[15]), "+f"(d[16]), "+f"(d[17]), "+f"(d[18]), "+f"(d[19]), "+f"(d[20]), "+f"(d[21]), "+f"(d[22]), "+f"(d[23]), "+f"(d[24]), "+f"(d[25]), "+f"(d[26]), "+f"(d[27]), "+f"(d[28]), "+f"(d[29]), "+f"(d[30]), "+f"(d[31]), "+f"(d[32]), "+f"(d[33]), "+f"(d[34]), "+f"(d[35]), "+f"(d[36]), "+f"(d[37]), "+f"(d[38]), "+f"(d[39]), "+f"(d[40]), "+f"(d[41]), "+f"(d[42]), "+f"(d[43]), "+f"(d[44]), "+f"(d[45]), "+f"(d[46]), "+f"(d[47]), "+f"(d[48]), "+f"(d[49]), "+f"(d[50]), "+f"(d[51]), "+f"(d[52]), "+f"(d[53]), "+f"(d[54]), "+f"(d[55]), "+f"(d[56]), "+f"(d[57]), "+f"(d[58]), "+f"(d[59]), "+f"(d[60]), "+f"(d[61]), "+f"(d[62]), "+f"(d[63]), "+f"(d[64]), "+f"(d[65]), "+f"(d[66]), "+f"(d[67]), "+f"(d[68]), "+f"(d[69]), "+f"(d[70]), "+f"(d[71]), "+f"(d[72]), "+f"(d[73]), "+f"(d[74]), "+f"(d[75]), "+f"(d[76]), "+f"(d[77]), "+f"(d[78]), "+f"(d[79]), "+f"(d[80]), "+f"(d[81]), "+f"(d[82]), "+f"(d[83]), "+f"(d[84]), "+f"(d[85]), "+f"(d[86]), "+f"(d[87]), "+f"(d[88]), "+f"(d[89]), "+f"(d[90]), "+f"(d[91]), "+f"(d[92]), "+f"(d[93]), "+f"(d[94]), "+f"(d[95])
    : "l"(da), "l"(db), "r"(scale_d));
}

__device__ __forceinline__ void wgmma_n256(float (&d)[128], uint64_t da, uint64_t db, int scale_d) {
  asm volatile("{\n.reg .pred p;\nsetp.ne.b32 p, %130, 0;\n"
    "wgmma.mma_async.sync.aligned.m64n256k16.f32.bf16.bf16 {%0, %1, %2, %3, %4, %5, %6, %7, %8, %9, %10, %11, %12, %13, %14, %15, %16, %17, %18, %19, %20, %21, %22, %23, %24, %25, %26, %27, %28, %29, %30, %31, %32, %33, %34, %35, %36, %37, %38, %39, %40, %41, %42, %43, %44, %45, %46, %47, %48, %49, %50, %51, %52, %53, %54, %55, %56, %57, %58, %59, %60, %61, %62, %63, %64, %65, %66, %67, %68, %69, %70, %71, %72, %73, %74, %75, %76, %77, %78, %79, %80, %81, %82, %83, %84, %85, %86, %87, %88, %89, %90, %91, %92, %93, %94, %95, %96, %97, %98, %99, %100, %101, %102, %103, %104, %105, %106, %107, %108, %109, %110, %111, %112, %113, %114, %115, %116, %117, %118, %119, %120, %121, %122, %123, %124, %125, %126, %127}, %128, %129, p, 1, 1, 0, 1;\n}\n"
    : "+f"(d[0]), "+f"(d[1]), "+f"(d[2]), "+f"(d[3]), "+f"(d[4]), "+f"(d[5]), "+f"(d[6]), "+f"(d[7]), "+f"(d[8]), "+f"(d[9]), "+f"(d[10]), "+f"(d[11]), "+f"(d[12]), "+f"(d[13]), "+f"(d[14]), "+f"(d[15]), "+f"(d[16]), "+f"(d[17]), "+f"(d[18]), "+f"(d[19]), "+f"(d[20]), "+f"(d[21]), "+f"(d[22]), "+f"(d[23]), "+f"(d[24]), "+f"(d[25]), "+f"(d[26]), "+f"(d[27]), "+f"(d[28]), "+f"(d[29]), "+f"(d[30]), "+f"(d[31]), "+f"(d[32]), "+f"(d[33]), "+f"(d[34]), "+f"(d[35]), "+f"(d[36]), "+f"(d[37]), "+f"(d[38]), "+f"(d[39]), "+f"(d[40]), "+f"(d[41]), "+f"(d[42]), "+f"(d[43]), "+f"(d[44]), "+f"(d[45]), "+f"(d[46]), "+f"(d[47]), "+f"(d[48]), "+f"(d[49]), "+f"(d[50]), "+f"(d[51]), "+f"(d[52]), "+f"(d[53]), "+f"(d[54]), "+f"(d[55]), "+f"(d[56]), "+f"(d[57]), "+f"(d[58]), "+f"(d[59]), "+f"(d[60]), "+f"(d[61]), "+f"(d[62]), "+f"(d[63]), "+f"(d[64]), "+f"(d[65]), "+f"(d[66]), "+f"(d[67]), "+f"(d[68]), "+f"(d[69]), "+f"(d[70]), "+f"(d[71]), "+f"(d[72]), "+f"(d[73]), "+f"(d[74]), "+f"(d[75]), "+f"(d[76]), "+f"(d[77]), "+f"(d[78]), "+f"(d[79]), "+f"(d[80]), "+f"(d[81]), "+f"(d[82]), "+f"(d[83]), "+f"(d[84]), "+f"(d[85]), "+f"(d[86]), "+f"(d[87]), "+f"(d[88]), "+f"(d[89]), "+f"(d[90]), "+f"(d[91]), "+f"(d[92]), "+f"(d[93]), "+f"(d[94]), "+f"(d[95]), "+f"(d[96]), "+f"(d[97]), "+f"(d[98]), "+f"(d[99]), "+f"(d[100]), "+f"(d[101]), "+f"(d[102]), "+f"(d[103]), "+f"(d[104]), "+f"(d[105]), "+f"(d[106]), "+f"(d[107]), "+f"(d[108]), "+f"(d[109]), "+f"(d[110]), "+f"(d[111]), "+f"(d[112]), "+f"(d[113]), "+f"(d[114]), "+f"(d[115]), "+f"(d[116]), "+f"(d[117]), "+f"(d[118]), "+f"(d[119]), "+f"(d[120]), "+f"(d[121]), "+f"(d[122]), "+f"(d[123]), "+f"(d[124]), "+f"(d[125]), "+f"(d[126]), "+f"(d[127])
    : "l"(da), "l"(db), "r"(scale_d));
}

__device__ __forceinline__ void wgmma_rs_n128(float (&d)[64], const uint32_t (&a)[4], uint64_t db) {
  asm volatile(
    "wgmma.mma_async.sync.aligned.m64n128k16.f32.bf16.bf16 {%0, %1, %2, %3, %4, %5, %6, %7, %8, %9, %10, %11, %12, %13, %14, %15, %16, %17, %18, %19, %20, %21, %22, %23, %24, %25, %26, %27, %28, %29, %30, %31, %32, %33, %34, %35, %36, %37, %38, %39, %40, %41, %42, %43, %44, %45, %46, %47, %48, %49, %50, %51, %52, %53, %54, %55, %56, %57, %58, %59, %60, %61, %62, %63}, {%64, %65, %66, %67}, %68, 1, 1, 1, 1;\n"
    : "+f"(d[0]), "+f"(d[1]), "+f"(d[2]), "+f"(d[3]), "+f"(d[4]), "+f"(d[5]), "+f"(d[6]), "+f"(d[7]), "+f"(d[8]), "+f"(d[9]), "+f"(d[10]), "+f"(d[11]), "+f"(d[12]), "+f"(d[13]), "+f"(d[14]), "+f"(d[15]), "+f"(d[16]), "+f"(d[17]), "+f"(d[18]), "+f"(d[19]), "+f"(d[20]), "+f"(d[21]), "+f"(d[22]), "+f"(d[23]), "+f"(d[24]), "+f"(d[25]), "+f"(d[26]), "+f"(d[27]), "+f"(d[28]), "+f"(d[29]), "+f"(d[30]), "+f"(d[31]), "+f"(d[32]), "+f"(d[33]), "+f"(d[34]), "+f"(d[35]), "+f"(d[36]), "+f"(d[37]), "+f"(d[38]), "+f"(d[39]), "+f"(d[40]), "+f"(d[41]), "+f"(d[42]), "+f"(d[43]), "+f"(d[44]), "+f"(d[45]), "+f"(d[46]), "+f"(d[47]), "+f"(d[48]), "+f"(d[49]), "+f"(d[50]), "+f"(d[51]), "+f"(d[52]), "+f"(d[53]), "+f"(d[54]), "+f"(d[55]), "+f"(d[56]), "+f"(d[57]), "+f"(d[58]), "+f"(d[59]), "+f"(d[60]), "+f"(d[61]), "+f"(d[62]), "+f"(d[63])
    : "r"(a[0]), "r"(a[1]), "r"(a[2]), "r"(a[3]), "l"(db));
}

__device__ __forceinline__ void wgmma_rs_n192(float (&d)[96], const uint32_t (&a)[4], uint64_t db) {
  asm volatile(
    "wgmma.mma_async.sync.aligned.m64n192k16.f32.bf16.bf16 {%0, %1, %2, %3, %4, %5, %6, %7, %8, %9, %10, %11, %12, %13, %14, %15, %16, %17, %18, %19, %20, %21, %22, %23, %24, %25, %26, %27, %28, %29, %30, %31, %32, %33, %34, %35, %36, %37, %38, %39, %40, %41, %42, %43, %44, %45, %46, %47, %48, %49, %50, %51, %52, %53, %54, %55, %56, %57, %58, %59, %60, %61, %62, %63, %64, %65, %66, %67, %68, %69, %70, %71, %72, %73, %74, %75, %76, %77, %78, %79, %80, %81, %82, %83, %84, %85, %86, %87, %88, %89, %90, %91, %92, %93, %94, %95}, {%96, %97, %98, %99}, %100, 1, 1, 1, 1;\n"
    : "+f"(d[0]), "+f"(d[1]), "+f"(d[2]), "+f"(d[3]), "+f"(d[4]), "+f"(d[5]), "+f"(d[6]), "+f"(d[7]), "+f"(d[8]), "+f"(d[9]), "+f"(d[10]), "+f"(d[11]), "+f"(d[12]), "+f"(d[13]), "+f"(d[14]), "+f"(d[15]), "+f"(d[16]), "+f"(d[17]), "+f"(d[18]), "+f"(d[19]), "+f"(d[20]), "+f"(d[21]), "+f"(d[22]), "+f"(d[23]), "+f"(d[24]), "+f"(d[25]), "+f"(d[26]), "+f"(d[27]), "+f"(d[28]), "+f"(d[29]), "+f"(d[30]), "+f"(d[31]), "+f"(d[32]), "+f"(d[33]), "+f"(d[34]), "+f"(d[35]), "+f"(d[36]), "+f"(d[37]), "+f"(d[38]), "+f"(d[39]), "+f"(d[40]), "+f"(d[41]), "+f"(d[42]), "+f"(d[43]), "+f"(d[44]), "+f"(d[45]), "+f"(d[46]), "+f"(d[47]), "+f"(d[48]), "+f"(d[49]), "+f"(d[50]), "+f"(d[51]), "+f"(d[52]), "+f"(d[53]), "+f"(d[54]), "+f"(d[55]), "+f"(d[56]), "+f"(d[57]), "+f"(d[58]), "+f"(d[59]), "+f"(d[60]), "+f"(d[61]), "+f"(d[62]), "+f"(d[63]), "+f"(d[64]), "+f"(d[65]), "+f"(d[66]), "+f"(d[67]), "+f"(d[68]), "+f"(d[69]), "+f"(d[70]), "+f"(d[71]), "+f"(d[72]), "+f"(d[73]), "+f"(d[74]), "+f"(d[75]), "+f"(d[76]), "+f"(d[77]), "+f"(d[78]), "+f"(d[79]), "+f"(d[80]), "+f"(d[81]), "+f"(d[82]), "+f"(d[83]), "+f"(d[84]), "+f"(d[85]), "+f"(d[86]), "+f"(d[87]), "+f"(d[88]), "+f"(d[89]), "+f"(d[90]), "+f"(d[91]), "+f"(d[92]), "+f"(d[93]), "+f"(d[94]), "+f"(d[95])
    : "r"(a[0]), "r"(a[1]), "r"(a[2]), "r"(a[3]), "l"(db));
}

__device__ __forceinline__ void wgmma_rs_n256(float (&d)[128], const uint32_t (&a)[4], uint64_t db) {
  asm volatile(
    "wgmma.mma_async.sync.aligned.m64n256k16.f32.bf16.bf16 {%0, %1, %2, %3, %4, %5, %6, %7, %8, %9, %10, %11, %12, %13, %14, %15, %16, %17, %18, %19, %20, %21, %22, %23, %24, %25, %26, %27, %28, %29, %30, %31, %32, %33, %34, %35, %36, %37, %38, %39, %40, %41, %42, %43, %44, %45, %46, %47, %48, %49, %50, %51, %52, %53, %54, %55, %56, %57, %58, %59, %60, %61, %62, %63, %64, %65, %66, %67, %68, %69, %70, %71, %72, %73, %74, %75, %76, %77, %78, %79, %80, %81, %82, %83, %84, %85, %86, %87, %88, %89, %90, %91, %92, %93, %94, %95, %96, %97, %98, %99, %100, %101, %102, %103, %104, %105, %106, %107, %108, %109, %110, %111, %112, %113, %114, %115, %116, %117, %118, %119, %120, %121, %122, %123, %124, %125, %126, %127}, {%128, %129, %130, %131}, %132, 1, 1, 1, 1;\n"
    : "+f"(d[0]), "+f"(d[1]), "+f"(d[2]), "+f"(d[3]), "+f"(d[4]), "+f"(d[5]), "+f"(d[6]), "+f"(d[7]), "+f"(d[8]), "+f"(d[9]), "+f"(d[10]), "+f"(d[11]), "+f"(d[12]), "+f"(d[13]), "+f"(d[14]), "+f"(d[15]), "+f"(d[16]), "+f"(d[17]), "+f"(d[18]), "+f"(d[19]), "+f"(d[20]), "+f"(d[21]), "+f"(d[22]), "+f"(d[23]), "+f"(d[24]), "+f"(d[25]), "+f"(d[26]), "+f"(d[27]), "+f"(d[28]), "+f"(d[29]), "+f"(d[30]), "+f"(d[31]), "+f"(d[32]), "+f"(d[33]), "+f"(d[34]), "+f"(d[35]), "+f"(d[36]), "+f"(d[37]), "+f"(d[38]), "+f"(d[39]), "+f"(d[40]), "+f"(d[41]), "+f"(d[42]), "+f"(d[43]), "+f"(d[44]), "+f"(d[45]), "+f"(d[46]), "+f"(d[47]), "+f"(d[48]), "+f"(d[49]), "+f"(d[50]), "+f"(d[51]), "+f"(d[52]), "+f"(d[53]), "+f"(d[54]), "+f"(d[55]), "+f"(d[56]), "+f"(d[57]), "+f"(d[58]), "+f"(d[59]), "+f"(d[60]), "+f"(d[61]), "+f"(d[62]), "+f"(d[63]), "+f"(d[64]), "+f"(d[65]), "+f"(d[66]), "+f"(d[67]), "+f"(d[68]), "+f"(d[69]), "+f"(d[70]), "+f"(d[71]), "+f"(d[72]), "+f"(d[73]), "+f"(d[74]), "+f"(d[75]), "+f"(d[76]), "+f"(d[77]), "+f"(d[78]), "+f"(d[79]), "+f"(d[80]), "+f"(d[81]), "+f"(d[82]), "+f"(d[83]), "+f"(d[84]), "+f"(d[85]), "+f"(d[86]), "+f"(d[87]), "+f"(d[88]), "+f"(d[89]), "+f"(d[90]), "+f"(d[91]), "+f"(d[92]), "+f"(d[93]), "+f"(d[94]), "+f"(d[95]), "+f"(d[96]), "+f"(d[97]), "+f"(d[98]), "+f"(d[99]), "+f"(d[100]), "+f"(d[101]), "+f"(d[102]), "+f"(d[103]), "+f"(d[104]), "+f"(d[105]), "+f"(d[106]), "+f"(d[107]), "+f"(d[108]), "+f"(d[109]), "+f"(d[110]), "+f"(d[111]), "+f"(d[112]), "+f"(d[113]), "+f"(d[114]), "+f"(d[115]), "+f"(d[116]), "+f"(d[117]), "+f"(d[118]), "+f"(d[119]), "+f"(d[120]), "+f"(d[121]), "+f"(d[122]), "+f"(d[123]), "+f"(d[124]), "+f"(d[125]), "+f"(d[126]), "+f"(d[127])
    : "r"(a[0]), "r"(a[1]), "r"(a[2]), "r"(a[3]), "l"(db));
}

__device__ __forceinline__ uint32_t smem_u32(const void* p) { return (uint32_t)__cvta_generic_to_shared(p); }
__device__ __forceinline__ void mbar_init(uint32_t a, uint32_t cnt) { asm volatile("mbarrier.init.shared::cta.b64 [%0], %1;" ::"r"(a), "r"(cnt)); }
__device__ __forceinline__ void mbar_expect_tx(uint32_t a, uint32_t bytes) {
  asm volatile("mbarrier.arrive.expect_tx.shared::cta.b64 _, [%0], %1;" ::"r"(a), "r"(bytes) : "memory");
}
__device__ __forceinline__ void mbar_arrive_cluster(uint32_t a, uint32_t cta) {
  asm volatile("{\n.reg .b32 ra;\nmapa.shared::cluster.u32 ra, %0, %1;\nmbarrier.arrive.shared::cluster.b64 _, [ra];\n}\n" ::"r"(a), "r"(cta) : "memory");
}
__device__ __forceinline__ void mbar_arrive_both(uint32_t a) {
  mbar_arrive_cluster(a, 0); mbar_arrive_cluster(a, 1);
}
__device__ __forceinline__ void mbar_wait(uint32_t a, uint32_t parity, int code) {
  asm volatile("{\n.reg .pred p, q;\n.reg .u32 c;\nmov.u32 c, 0;\n"
               "LW:\nmbarrier.try_wait.parity.shared::cta.b64 p, [%0], %1;\n@p bra DW;\n"
               "add.u32 c, c, 1;\nsetp.lt.u32 q, c, 0x4000000;\n@q bra LW;\ntrap;\nDW:\n}\n" ::"r"(a), "r"(parity) : "memory");
}
__device__ __forceinline__ bool mbar_test(uint32_t a, uint32_t parity) {
  uint32_t ok;
  asm volatile("{\n.reg .pred p;\nmbarrier.test_wait.parity.shared::cta.b64 p, [%1], %2;\nselp.u32 %0, 1, 0, p;\n}\n" : "=r"(ok) : "r"(a), "r"(parity) : "memory");
  return __all_sync(0xffffffffu, ok != 0);
}
__device__ __forceinline__ void tma_load_2d(uint32_t dst, const CUtensorMap* map, int c0, int c1, uint32_t mbar) {
  asm volatile("cp.async.bulk.tensor.2d.shared::cluster.global.mbarrier::complete_tx::bytes [%0], [%1, {%3, %4}], [%2];" ::"r"(dst), "l"(map), "r"(mbar), "r"(c0), "r"(c1) : "memory");
}
__device__ __forceinline__ void tma_load_2d_mc(uint32_t dst, const CUtensorMap* map, int c0, int c1, uint32_t mbar, uint16_t mask) {
  asm volatile("cp.async.bulk.tensor.2d.shared::cluster.global.mbarrier::complete_tx::bytes.multicast::cluster [%0], [%1, {%3, %4}], [%2], %5;" ::"r"(dst), "l"(map), "r"(mbar), "r"(c0), "r"(c1), "h"(mask) : "memory");
}
__device__ __forceinline__ void tma_load_3d_mc(uint32_t dst, const CUtensorMap* map, int c0, int c1, int c2, uint32_t mbar, uint16_t mask) {
  asm volatile("cp.async.bulk.tensor.3d.shared::cluster.global.mbarrier::complete_tx::bytes.multicast::cluster [%0], [%1, {%3, %4, %5}], [%2], %6;" ::"r"(dst), "l"(map), "r"(mbar), "r"(c0), "r"(c1), "r"(c2), "h"(mask) : "memory");
}
__device__ __forceinline__ void tma_prefetch_3d(const CUtensorMap* map, int c0, int c1, int c2) {
  asm volatile("cp.async.bulk.prefetch.tensor.3d.L2.global.tile [%0, {%1, %2, %3}];" ::"l"(map), "r"(c0), "r"(c1), "r"(c2) : "memory");
}
__device__ __forceinline__ void wgmma_fence() { asm volatile("wgmma.fence.sync.aligned;" ::: "memory"); }
__device__ __forceinline__ void wgmma_fence_nm() { asm volatile("wgmma.fence.sync.aligned;"); }
__device__ __forceinline__ void wgmma_commit() { asm volatile("wgmma.commit_group.sync.aligned;" ::: "memory"); }
template <int N> __device__ __forceinline__ void wgmma_wait() { asm volatile("wgmma.wait_group.sync.aligned %0;" ::"n"(N) : "memory"); }
__device__ __forceinline__ uint64_t make_desc(uint32_t saddr, uint32_t lbo, uint32_t sbo) {
  return (uint64_t)((saddr & 0x3FFFF) >> 4) | ((uint64_t)(lbo >> 4) << 16) | ((uint64_t)(sbo >> 4) << 32) | (1ull << 62);
}
__device__ __forceinline__ void fence_proxy_async() { asm volatile("fence.proxy.async.global;" ::: "memory"); }
__device__ __forceinline__ void named_bar(int id, int n) { asm volatile("bar.sync %0, %1;" ::"r"(id), "r"(n) : "memory"); }
__device__ __forceinline__ void cluster_sync() {
  asm volatile("barrier.cluster.arrive.release.aligned;\nbarrier.cluster.wait.acquire.aligned;" ::: "memory");
}
__device__ __forceinline__ unsigned ld_acquire(const unsigned* p) {
  unsigned v;
  asm volatile("ld.acquire.gpu.global.u32 %0, [%1];" : "=r"(v) : "l"(p) : "memory");
  return v;
}
__device__ __forceinline__ unsigned flag_wait(const unsigned* p, unsigned target, int code) {
#pragma unroll 1
  for (uint32_t it = 0; it < SPIN_MAX; ++it) {
    unsigned v = ld_acquire(p);
    if (v >= target) return v;
    __nanosleep(20);
  }
  FAIL(code);
  return 0;
}
__device__ __forceinline__ void warp_flag_wait(const unsigned* p, unsigned target) {
#pragma unroll 1
  for (uint32_t it = 0; it < (1u << 24); ++it) {
    if (__all_sync(0xffffffffu, ld_acquire(p) >= target)) return;
    __nanosleep(20);
  }
  __trap();
}
__device__ __forceinline__ void flag_add(unsigned* p) {
  asm volatile("red.release.gpu.global.add.u32 [%0], 1;" ::"l"(p) : "memory");
}
__device__ __forceinline__ void agent_exit() {
  __threadfence();
  unsigned old = atomicAdd(&g_flags[272], 1u);
  if (old == NAGENTS - 1) {
    for (int i = 0; i < 273; ++i) g_flags[i] = 0;
    __threadfence();
  }
}
__device__ __forceinline__ float bf16r(float v) { return __bfloat162float(__float2bfloat16_rn(v)); }
__device__ __forceinline__ uint32_t pack_bf16(float lo, float hi) {
  uint32_t r;
  asm("cvt.rn.bf16x2.f32 %0, %1, %2;" : "=r"(r) : "f"(hi), "f"(lo));
  return r;
}
__device__ __forceinline__ void quad_transpose(uint32_t& v0, uint32_t& v1, uint32_t& v2, uint32_t& v3, int q) {
  bool b0 = q & 1;
  uint32_t s0 = b0 ? v0 : v1, s1 = b0 ? v2 : v3;
  s0 = __shfl_xor_sync(0xffffffffu, s0, 1);
  s1 = __shfl_xor_sync(0xffffffffu, s1, 1);
  if (b0) { v0 = s0; v2 = s1; } else { v1 = s0; v3 = s1; }
  bool b1 = q & 2;
  s0 = b1 ? v0 : v2; s1 = b1 ? v1 : v3;
  s0 = __shfl_xor_sync(0xffffffffu, s0, 2);
  s1 = __shfl_xor_sync(0xffffffffu, s1, 2);
  if (b1) { v0 = s0; v1 = s1; } else { v2 = s0; v3 = s1; }
}

struct Tile { int is_h; int col; int nb; };
__device__ __forceinline__ int num_tiles(int j) { return j ? 6 : 5; }
__device__ __forceinline__ Tile get_tile(int p, int j, int t) {
  Tile T;
  if (t == 0) {
    T.is_h = 0;
    if (j == 0) { T.col = 256 * p; T.nb = 4; }
    else { T.col = 1024 + 192 * p; T.nb = (p == 3) ? 2 : 3; }
  } else {
    T.is_h = 1; T.col = 128 * (9 * p + (j ? 4 : 0) + (t - 1)); T.nb = 4;
  }
  return T;
}

template <int NB> struct Acc { float a[NB * 32]; };
template <int NB> __device__ __forceinline__ void wgmma_nb(float (&d)[NB * 32], uint64_t da, uint64_t db, int sc);
template <> __device__ __forceinline__ void wgmma_nb<2>(float (&d)[64], uint64_t da, uint64_t db, int sc) { wgmma_n128(d, da, db, sc); }
template <> __device__ __forceinline__ void wgmma_nb<3>(float (&d)[96], uint64_t da, uint64_t db, int sc) { wgmma_n192(d, da, db, sc); }
template <> __device__ __forceinline__ void wgmma_nb<4>(float (&d)[128], uint64_t da, uint64_t db, int sc) { wgmma_n256(d, da, db, sc); }
template <int NB> __device__ __forceinline__ void wgmma_rs_nb(float (&d)[NB * 32], const uint32_t (&a)[4], uint64_t db);
template <> __device__ __forceinline__ void wgmma_rs_nb<2>(float (&d)[64], const uint32_t (&a)[4], uint64_t db) { wgmma_rs_n128(d, a, db); }
template <> __device__ __forceinline__ void wgmma_rs_nb<3>(float (&d)[96], const uint32_t (&a)[4], uint64_t db) { wgmma_rs_n192(d, a, db); }
template <> __device__ __forceinline__ void wgmma_rs_nb<4>(float (&d)[128], const uint32_t (&a)[4], uint64_t db) { wgmma_rs_n256(d, a, db); }

struct Ctx {
  uint32_t sbase;
  uint32_t full1, empty1, full2, empty2;
  uint32_t peer;
  int wg;
  int tid;
};

__device__ __forceinline__ void publish(unsigned* flag) {
  __threadfence();
  __syncwarp();
  if ((threadIdx.x & 31) == 0) flag_add(flag);
}
__device__ __forceinline__ void release2(const Ctx& c, uint32_t sa, uint32_t sb) {
  if (c.tid < 4) mbar_arrive_cluster(c.empty1 + 8 * ((c.tid & 2) ? sb : sa), c.tid & 1);
}
template <int NB>
__device__ __forceinline__ void g1_tile(const Ctx& c, float (&acc)[NB * 32], const int t  , const uint32_t (&areg)[8][4]) {
  const uint32_t abase = c.sbase + c.wg * 8192;
  wgmma_fence();
  uint32_t s = (uint32_t)(18 * t) % NS1, ph = ((uint32_t)(18 * t) / NS1) & 1, sp = 0;
#pragma unroll 1
  for (int kb = 0; kb < 14; ++kb) {
    mbar_wait(c.full1 + 8 * s, ph, 0);
    const uint32_t a0 = abase + (kb >> 1) * 16384 + (kb & 1) * 64;
    const uint32_t b0 = c.sbase + slot1_off(s);
    wgmma_nb<NB>(acc, make_desc(a0, 16, 1024), make_desc(b0, 4096, 1024), kb > 0);
    wgmma_nb<NB>(acc, make_desc(a0 + 32, 16, 1024), make_desc(b0 + 2048, 4096, 1024), 1);
    wgmma_commit();
    wgmma_wait<1>();
    if (kb > 0 && c.tid < 2) mbar_arrive_cluster(c.empty1 + 8 * sp, c.tid);
    sp = s;
    if (++s == NS1) { s = 0; ph ^= 1; }
  }
#pragma unroll
  for (int kk = 0; kk < 4; ++kk) {
    mbar_wait(c.full1 + 8 * s, ph, 0);
    const uint32_t b0 = c.sbase + slot1_off(s);
    wgmma_rs_nb<NB>(acc, areg[2 * kk], make_desc(b0, 4096, 1024));
    wgmma_rs_nb<NB>(acc, areg[2 * kk + 1], make_desc(b0 + 2048, 4096, 1024));
    wgmma_commit();
    wgmma_wait<1>();
    if (c.tid < 2) mbar_arrive_cluster(c.empty1 + 8 * sp, c.tid);
    sp = s;
    if (++s == NS1) { s = 0; ph ^= 1; }
  }
  wgmma_wait<0>();
  if (c.tid < 2) mbar_arrive_cluster(c.empty1 + 8 * sp, c.tid);
}

template <int NB>
__device__ __forceinline__ void epi_h(const Ctx& c, float (&acc)[NB * 32], int row0  , int hcol) {
  constexpr int G = NB * 4;
  const int lane = c.tid & 31, w = c.tid >> 5, q = lane & 3;
  const int r = row0 + c.wg * 64 + w * 16 + (lane >> 2);
  __nv_bfloat16* dst0 = g_act + (size_t)r * ACT_ + 576 + hcol + q * 8;
  __nv_bfloat16* dst1 = dst0 + 8 * ACT_;
  const __nv_bfloat162 zero2 = __floats2bfloat162_rn(0.f, 0.f);
#pragma unroll
  for (int a = 0; a < G / 4; ++a) {
    uint32_t v[4], u[4];
#pragma unroll
    for (int i = 0; i < 4; ++i) {
      int g = 4 * a + i;
      uint32_t g0 = pack_bf16(acc[4 * g], acc[4 * g + 1]), g1 = pack_bf16(acc[4 * g + 2], acc[4 * g + 3]);
      uint32_t u0 = pack_bf16(acc[4 * (g + G)], acc[4 * (g + G) + 1]), u1 = pack_bf16(acc[4 * (g + G) + 2], acc[4 * (g + G) + 3]);
      __nv_bfloat162 h0 = __hmul2(__hmax2(*(__nv_bfloat162*)&g0, zero2), *(__nv_bfloat162*)&u0);
      __nv_bfloat162 h1 = __hmul2(__hmax2(*(__nv_bfloat162*)&g1, zero2), *(__nv_bfloat162*)&u1);
      v[i] = *(uint32_t*)&h0; u[i] = *(uint32_t*)&h1;
    }
    quad_transpose(v[0], v[1], v[2], v[3], q);
    quad_transpose(u[0], u[1], u[2], u[3], q);
    *(uint4*)(dst0 + a * 32) = make_uint4(v[0], v[1], v[2], v[3]);
    *(uint4*)(dst1 + a * 32) = make_uint4(u[0], u[1], u[2], u[3]);
  }
}
template <int NB>
__device__ __forceinline__ void epi_qkv(const Ctx& c, float (&acc)[NB * 32], int row0, int col) {
  constexpr int G = NB * 8;
  const int lane = c.tid & 31, w = c.tid >> 5, q = lane & 3;
  const int r = row0 + c.wg * 64 + w * 16 + (lane >> 2);
  __nv_bfloat16* dst0 = g_qkv + (size_t)r * QKV_ + col + q * 8;
  __nv_bfloat16* dst1 = dst0 + 8 * QKV_;
#pragma unroll
  for (int a = 0; a < G / 4; ++a) {
    uint32_t v[4], u[4];
#pragma unroll
    for (int i = 0; i < 4; ++i) {
      int g = 4 * a + i;
      v[i] = pack_bf16(acc[4 * g], acc[4 * g + 1]); u[i] = pack_bf16(acc[4 * g + 2], acc[4 * g + 3]);
    }
    quad_transpose(v[0], v[1], v[2], v[3], q);
    quad_transpose(u[0], u[1], u[2], u[3], q);
    *(uint4*)(dst0 + a * 32) = make_uint4(v[0], v[1], v[2], v[3]);
    *(uint4*)(dst1 + a * 32) = make_uint4(u[0], u[1], u[2], u[3]);
  }
}
__device__ __forceinline__ void mbar_arrive_local(uint32_t a) { asm volatile("mbarrier.arrive.shared::cta.b64 _, [%0];" ::"r"(a) : "memory"); }

template <int NA>
__device__ __forceinline__ void acc_to_smem(float (&acc)[NA], uint32_t a0  , uint32_t pitch) {
#pragma unroll
  for (int g = 0; g < NA / 4; ++g) {
    asm volatile("st.shared.v2.f32 [%0], {%1, %2};" ::"r"(a0 + g * 32), "f"(acc[4 * g]), "f"(acc[4 * g + 1]) : "memory");
    asm volatile("st.shared.v2.f32 [%0], {%1, %2};" ::"r"(a0 + 8 * pitch + g * 32), "f"(acc[4 * g + 2]), "f"(acc[4 * g + 3]) : "memory");
  }
}
__device__ __forceinline__ float4 lds128(uint32_t a) {
  float4 v;
  asm volatile("ld.shared.v4.f32 {%0, %1, %2, %3}, [%4];" : "=f"(v.x), "=f"(v.y), "=f"(v.z), "=f"(v.w) : "r"(a));
  return v;
}

__device__ __forceinline__ void mma16816(float (&c)[4], uint32_t a0, uint32_t a1, uint32_t a2, uint32_t a3, uint32_t b0, uint32_t b1) {
  asm volatile("mma.sync.aligned.m16n8k16.row.col.f32.bf16.bf16.f32 {%0,%1,%2,%3}, {%4,%5,%6,%7}, {%8,%9}, {%0,%1,%2,%3};"
               : "+f"(c[0]), "+f"(c[1]), "+f"(c[2]), "+f"(c[3]) : "r"(a0), "r"(a1), "r"(a2), "r"(a3), "r"(b0), "r"(b1));
}
__device__ __forceinline__ uint32_t movm(uint32_t a) {
  uint32_t d;
  asm volatile("movmatrix.sync.aligned.m8n8.trans.b16 %0, %1;" : "=r"(d) : "r"(a));
  return d;
}
struct HeadRegs { uint32_t q[2][3], k[4][3], v[4][3]; };
__device__ __forceinline__ void load_head(HeadRegs& R, int h, int qrow, int g, int t) {
  const int o = h & 1;
  const int wp = 9 * h + o + 2 * t, wt = 9 * h + (o ? 0 : 8);
#pragma unroll
  for (int r = 0; r < 2; ++r) {
    const uint32_t* p = (const uint32_t*)(g_qkv + (size_t)(qrow + g + 8 * r) * QKV_);
    uint2 a = *(const uint2*)(p + wp);
    R.q[r][0] = a.x; R.q[r][1] = a.y; R.q[r][2] = t == 0 ? p[wt] : 0u;
  }
#pragma unroll
  for (int nt = 0; nt < 4; ++nt) {
    const int jj = 8 * nt + g, kr = qrow - 14 + jj;
    const bool ok = (kr >= 0) && (jj < 30);
    const uint32_t* p = (const uint32_t*)(g_qkv + (size_t)(ok ? kr : qrow) * QKV_);
    uint2 a = make_uint2(0u, 0u);
    if (ok) a = *(const uint2*)(p + 288 + wp);
    R.k[nt][0] = a.x; R.k[nt][1] = a.y; R.k[nt][2] = (ok && t == 0) ? p[288 + wt] : 0u;
    R.v[nt][0] = ok ? p[576 + 9 * h + t] : 0u; R.v[nt][1] = ok ? p[576 + 9 * h + 4 + t] : 0u;
    R.v[nt][2] = (ok && t == 0) ? p[576 + 9 * h + 8] : 0u;
  }
}
__device__ __noinline__ void attention(int row0, int role, int m, int aw, int lane) {
  warp_flag_wait(&g_flags[((lane >= 8 && role == 0 && m > 0) ? m - 1 : m) * 8 + (lane & 7)], 1);
  if (aw == 0 && lane == 0) TS2(24);
  const float scale = 0.23570226039551584f;
  const int g = lane >> 2, t = lane & 3;
  const int qrow = row0 + role * 16;
  HeadRegs N;
  load_head(N, aw, qrow, g, t);
#pragma unroll 1
  for (int h = aw; h < 32; h += 8) {
    HeadRegs R = N;
    if (h + 8 < 32) load_head(N, h + 8, qrow, g, t);
    float sc[4][4];
#pragma unroll
    for (int nt = 0; nt < 4; ++nt) {
      sc[nt][0] = sc[nt][1] = sc[nt][2] = sc[nt][3] = 0.f;
      mma16816(sc[nt], R.q[0][0], R.q[1][0], R.q[0][1], R.q[1][1], R.k[nt][0], R.k[nt][1]);
      mma16816(sc[nt], R.q[0][2], R.q[1][2], 0u, 0u, R.k[nt][2], 0u);
    }
    const int par = g & 1;
    float l0[4], l1[4];
    float mx0 = -3.0e38f, mx1 = -3.0e38f;
#pragma unroll
    for (int nt = 0; nt < 4; ++nt) {
      const int jj = 8 * nt + 2 * t + par;
      const int d0 = g + 14 - jj, d1 = d0 + 8;
      const bool inr = qrow - 14 + jj >= 0;
      const bool ok0 = inr && d0 >= 0 && d0 <= 14, ok1 = inr && d1 >= 0 && d1 <= 14;
      uint32_t pk = pack_bf16(par ? sc[nt][1] : sc[nt][0], par ? sc[nt][3] : sc[nt][2]);
      pk = pack_bf16(__uint_as_float(pk << 16) * scale, __uint_as_float(pk & 0xffff0000u) * scale);
      l0[nt] = ok0 ? __uint_as_float(pk << 16) : -3.0e38f;
      l1[nt] = ok1 ? __uint_as_float(pk & 0xffff0000u) : -3.0e38f;
      mx0 = fmaxf(mx0, l0[nt]); mx1 = fmaxf(mx1, l1[nt]);
    }
    mx0 = fmaxf(mx0, __shfl_xor_sync(0xffffffffu, mx0, 1)); mx0 = fmaxf(mx0, __shfl_xor_sync(0xffffffffu, mx0, 2));
    mx1 = fmaxf(mx1, __shfl_xor_sync(0xffffffffu, mx1, 1)); mx1 = fmaxf(mx1, __shfl_xor_sync(0xffffffffu, mx1, 2));
    float s0 = 0.f, s1 = 0.f;
#pragma unroll
    for (int nt = 0; nt < 4; ++nt) {
      l0[nt] = __expf(l0[nt] - mx0); l1[nt] = __expf(l1[nt] - mx1);
      s0 += l0[nt]; s1 += l1[nt];
    }
    s0 += __shfl_xor_sync(0xffffffffu, s0, 1); s0 += __shfl_xor_sync(0xffffffffu, s0, 2);
    s1 += __shfl_xor_sync(0xffffffffu, s1, 1); s1 += __shfl_xor_sync(0xffffffffu, s1, 2);
    const float i0 = __frcp_rn(s0), i1 = __frcp_rn(s1);
    uint32_t pa[2][4];
#pragma unroll
    for (int nt = 0; nt < 4; ++nt) {
      const float p0 = l0[nt] * i0, p1 = l1[nt] * i1;
      pa[nt >> 1][(nt & 1) * 2] = par ? pack_bf16(0.f, p0) : pack_bf16(p0, 0.f);
      pa[nt >> 1][(nt & 1) * 2 + 1] = par ? pack_bf16(0.f, p1) : pack_bf16(p1, 0.f);
    }
    uint32_t* o0p = (uint32_t*)(g_act + (size_t)(qrow + g) * ACT_) + 9 * h;
    uint32_t* o1p = (uint32_t*)(g_act + (size_t)(qrow + g + 8) * ACT_) + 9 * h;
#pragma unroll
    for (int cg = 0; cg < 3; ++cg) {
      float oc[4] = {0.f, 0.f, 0.f, 0.f};
      mma16816(oc, pa[0][0], pa[0][1], pa[0][2], pa[0][3], movm(R.v[0][cg]), movm(R.v[1][cg]));
      mma16816(oc, pa[1][0], pa[1][1], pa[1][2], pa[1][3], movm(R.v[2][cg]), movm(R.v[3][cg]));
      if (cg < 2 || t == 0) {
        o0p[4 * cg + t] = pack_bf16(oc[0], oc[1]);
        o1p[4 * cg + t] = pack_bf16(oc[2], oc[3]);
      }
    }
  }
  if (aw == 0 && lane == 0) TS2(26);
}

__global__ void __cluster_dims__(2, 1, 1) __launch_bounds__(384, 1)
fused_kernel(const __grid_constant__ CUtensorMap m_qkv1, const __grid_constant__ CUtensorMap m_qkv2,
             const __grid_constant__ CUtensorMap m_gate2, const __grid_constant__ CUtensorMap m_up2,
             const __grid_constant__ CUtensorMap m_wo5, const __grid_constant__ CUtensorMap m_wo4,
             const __grid_constant__ CUtensorMap m_down5, const __grid_constant__ CUtensorMap m_down4,
             const __grid_constant__ CUtensorMap m_act,
             const __nv_bfloat16* __restrict__ x, __nv_bfloat16* __restrict__ out) {
  extern __shared__ uint8_t smem_raw[];
  const uint32_t sbase = (smem_u32(smem_raw) + 1023) & ~1023u;
  const uint32_t bars = sbase + DATA_BYTES;
  const uint32_t full1 = bars, empty1 = bars + 64, full2 = bars + 128, empty2 = bars + 192, pub = bars + 256;
  const int rank = blockIdx.x & 1, cl = blockIdx.x >> 1;
  const int role = cl & 7, m = (cl >> 3) * 2 + rank, p = role >> 1, j = role & 1;
  const int row0 = m * 128;
  const int warp = __shfl_sync(0xffffffffu, (int)(threadIdx.x >> 5), 0), lane = threadIdx.x & 31;
  const int nkb2 = (p == 3) ? 21 : 20;
  const int nblk2 = j ? 4 : 5;
  const int ncol0 = j ? 320 : 0;

  uint4 nx[9];
  if (warp >= 4) {
    const int cw = warp - 4;
    const uint4* src = (const uint4*)(x + (size_t)(row0 + cw * 16 + (lane >> 3)) * D_) + (lane & 7);
#pragma unroll
    for (int t = 0; t < 9; ++t) nx[t] = __ldg(src + 8 * t);
  }
  if (threadIdx.x == 0) {
    for (int s = 0; s < NS1; ++s) { mbar_init(full1 + 8 * s, 1); mbar_init(empty1 + 8 * s, MC ? 4 : 2); }
    for (int s = 0; s < NS2; ++s) { mbar_init(full2 + 8 * s, 1); mbar_init(empty2 + 8 * s, MC ? 4 : 2); }
    for (int s = 0; s < 7; ++s) mbar_init(pub + 8 * s, 256);
    asm volatile("fence.mbarrier_init.release.cluster;" ::: "memory");
  }
  __syncthreads();
  cluster_sync();

  if (warp < 4) {
    asm volatile("setmaxnreg.dec.sync.aligned.u32 40;");
    if (warp == 0) {
      if (lane == 0) {
        uint32_t it = 0;
        const int nt = num_tiles(j);
        volatile uint32_t* known = (volatile uint32_t*)(smem_raw + (bars + 320 - smem_u32(smem_raw)));
        volatile uint32_t* sched = known + 12;
        for (int t = 0; t < nt; ++t) {
          Tile T = get_tile(p, j, t);
          const CUtensorMap* mp; int cb, nmine;
          if (T.is_h) { mp = rank ? &m_up2 : &m_gate2; cb = T.col >> 6; nmine = 2; }
          else if (T.nb == 4) { mp = &m_qkv2; cb = (T.col >> 6) + 2 * rank; nmine = 2; }
          else if (T.nb == 3) { mp = rank ? &m_qkv1 : &m_qkv2; cb = (T.col >> 6) + 2 * rank; nmine = rank ? 1 : 2; }
          else { mp = &m_qkv1; cb = (T.col >> 6) + rank; nmine = 1; }
          const uint32_t doff = (T.nb == 2 ? rank : 2 * rank) * 4096;
          for (int kb = 0; kb < 18; ++kb, ++it) {
            uint32_t s = it % NS1, ph = (it / NS1) & 1;
            if (it == 5) {
              for (int r = 0; r < 9; ++r) known[r] = 0;
              const int hlo = p == 0 ? 0 : 20 * p - 9, hhi = 20 * p + 11 + (p == 3 ? 1 : 0);
              int n = 0;
              for (int tt = 1; tt <= 5; ++tt)
                for (int hb = hlo; hb < hhi; ++hb) {
                  int TT = hb >> 1, pp = TT / 9, idx = TT - 9 * pp;
                  int ot = 1 + (idx >= 4 ? idx - 4 : idx);
                  if (ot == tt) sched[n++] = (uint32_t)hb | ((uint32_t)(2 * pp + (idx >= 4)) << 8) | ((uint32_t)(ot + 1) << 16);
                }
            }
            mbar_wait(empty1 + 8 * s, s >= 5 ? ph : ph ^ 1, 1);
            mbar_expect_tx(full1 + 8 * s, T.nb * 4096);
            tma_load_3d_mc(sbase + slot1_off(s) + doff, mp, 0, kb * 32, cb, full1 + 8 * s, 3);
            (void)nmine;
          }
        }
        const CUtensorMap* mwo = j ? &m_wo4 : &m_wo5;
        const CUtensorMap* mdn = j ? &m_down4 : &m_down5;
        for (int i = 0; i < nkb2; ++i) {
          uint32_t s = i % NS2, ph = (i / NS2) & 1;
          int acol, kn, wrow; const CUtensorMap* mp; const unsigned* fl; unsigned tgt;
          if (p == 0 && i >= 11) {
            acol = (i - 11) * 64; mp = mwo; wrow = acol; fl = &g_flags[128 + m]; tgt = 8; kn = 8;
          } else {
            uint32_t e = sched[i];
            wrow = (e & 255) * 64; kn = (e >> 8) & 255; tgt = e >> 16;
            acol = 576 + wrow; mp = mdn; fl = &g_flags[m * 8 + kn];
          }
          mbar_wait(empty2 + 8 * s, ph, 2);
          mbar_expect_tx(full2 + 8 * s, 16384 + nblk2 * 8192);
          uint32_t dst = sbase + s * ST2_BYTES;
          tma_load_3d_mc(dst + 16384 + rank * nblk2 * 4096, mp, 0, wrow + 32 * rank, ncol0 >> 6, full2 + 8 * s, 3);
          if (known[kn] < tgt) { known[kn] = flag_wait(fl, tgt, 4); fence_proxy_async(); }
          tma_load_2d(dst, &m_act, acol, row0, full2 + 8 * s);
          TS2(32 + i);
        }
        agent_exit();
      }
    } else if (warp == 1) {
      const int nt = num_tiles(j);
      for (int t = 0; t < nt; ++t) {
        mbar_wait(pub + 8 * t, 0, 7);
        if (lane == 0) { if (t == 0) TS2(27); __threadfence(); flag_add(&g_flags[m * 8 + role]); if (t == 0) TS2(28); }
        __syncwarp();
        if (t == 1) {
          mbar_wait(pub + 8 * 6, 0, 7);
          if (lane == 0) { __threadfence(); flag_add(&g_flags[128 + m]); }
          __syncwarp();
        }
      }
      if (lane == 0) agent_exit();
    } else if (warp == 2) {
      if (lane == 0) {
        const int mp8 = cl >> 3, nt = num_tiles(j);
        for (int t = 1; t <= nt; ++t) {
          if (t >= 2) mbar_wait(pub + 8 * (t - 2), 0, 7);
          if (t < nt) {
            Tile T = get_tile(p, j, t);
            for (int kb = mp8; kb < 18; kb += 8) tma_prefetch_3d(rank ? &m_up2 : &m_gate2, 0, kb * 32, T.col >> 6);
          } else {
            const int hlo = p == 0 ? 0 : 20 * p - 9, hhi = 20 * p + 11 + (p == 3 ? 1 : 0);
            for (int hb = hlo + mp8; hb < hhi; hb += 8) tma_prefetch_3d(j ? &m_down4 : &m_down5, 0, hb * 64 + 32 * rank, ncol0 >> 6);
            if (p == 0) for (int ob = mp8; ob < 9; ob += 8) tma_prefetch_3d(j ? &m_wo4 : &m_wo5, 0, ob * 64 + 32 * rank, ncol0 >> 6);
          }
        }
      }
    }
  } else {
    asm volatile("setmaxnreg.inc.sync.aligned.u32 232;");
    Ctx c;
    c.sbase = sbase; c.full1 = full1; c.empty1 = empty1; c.full2 = full2; c.empty2 = empty2; c.peer = rank ^ 1;
    c.wg = (warp - 4) >> 2; c.tid = threadIdx.x - 128 - c.wg * 128;
    const int w = c.tid >> 5;
    if (c.wg == 0 && c.tid == 0) TS(0);
    uint32_t areg[8][4];
    {
      const int sub = lane >> 3, li = lane & 7;
#pragma unroll 1
      for (int itr = 0; itr < 4; ++itr) {
        const int r = c.wg * 64 + w * 16 + itr * 4 + sub;
        uint4 xv[9];
#pragma unroll
        for (int t = 0; t < 9; ++t) xv[t] = nx[t];
        if (itr < 3) {
          const uint4* src = (const uint4*)(x + (size_t)(row0 + r + 4) * D_) + li;
#pragma unroll
          for (int t = 0; t < 9; ++t) nx[t] = __ldg(src + 8 * t);
        }
        float s0 = 0.f, s1 = 0.f;
#pragma unroll
        for (int t = 0; t < 9; ++t) {
          const uint32_t* u = (const uint32_t*)&xv[t];
#pragma unroll
          for (int e = 0; e < 4; ++e) { s0 += __uint_as_float(u[e] << 16); s1 += __uint_as_float(u[e] & 0xffff0000u); }
        }
        float sum = s0 + s1;
        sum += __shfl_xor_sync(0xffffffffu, sum, 1); sum += __shfl_xor_sync(0xffffffffu, sum, 2); sum += __shfl_xor_sync(0xffffffffu, sum, 4);
        const float mean = sum * (1.f / 576.f);
        float q0 = 0.f, q1 = 0.f;
#pragma unroll
        for (int t = 0; t < 9; ++t) {
          const uint32_t* u = (const uint32_t*)&xv[t];
#pragma unroll
          for (int e = 0; e < 4; ++e) {
            float a = __uint_as_float(u[e] << 16) - mean, b = __uint_as_float(u[e] & 0xffff0000u) - mean;
            q0 = fmaf(a, a, q0); q1 = fmaf(b, b, q1);
          }
        }
        float sq = q0 + q1;
        sq += __shfl_xor_sync(0xffffffffu, sq, 1); sq += __shfl_xor_sync(0xffffffffu, sq, 2); sq += __shfl_xor_sync(0xffffffffu, sq, 4);
        const float vb = bf16r(sq * (1.f / 576.f));
        const float rinv = 1.f / bf16r(sqrtf(bf16r(vb + 1e-5f)));
        const __nv_bfloat162 mb2 = __float2bfloat162_rn(mean);
        const uint32_t dsta = sbase + r * 128 + ((li ^ (r & 7)) << 4);
#pragma unroll
        for (int t = 0; t < 9; ++t) {
          const uint32_t* u = (const uint32_t*)&xv[t];
          uint32_t o[4];
#pragma unroll
          for (int e = 0; e < 4; ++e) {
            __nv_bfloat162 d2 = __hsub2(*(const __nv_bfloat162*)&u[e], mb2);
            uint32_t du = *(uint32_t*)&d2;
            o[e] = pack_bf16(__uint_as_float(du << 16) * rinv, __uint_as_float(du & 0xffff0000u) * rinv);
          }
          asm volatile("st.shared.v4.b32 [%0], {%1, %2, %3, %4};" ::"r"(dsta + t * 16384), "r"(o[0]), "r"(o[1]), "r"(o[2]), "r"(o[3]) : "memory");
        }
      }
      asm volatile("fence.proxy.async.shared::cta;" ::: "memory");
      __syncwarp();
      {
        const int r = c.wg * 64 + w * 16 + (lane & 7) + ((lane >> 3) & 1) * 8;
        const int hi = lane >> 4;
#pragma unroll
        for (int ks = 0; ks < 8; ++ks) {
          const uint32_t ad = sbase + (7 + (ks >> 2)) * 16384 + r * 128 + ((((ks & 3) * 2 + hi) ^ (r & 7)) << 4);
          asm volatile("ldmatrix.sync.aligned.m8n8.x4.shared.b16 {%0, %1, %2, %3}, [%4];"
                       : "=r"(areg[ks][0]), "=r"(areg[ks][1]), "=r"(areg[ks][2]), "=r"(areg[ks][3]) : "r"(ad) : "memory");
        }
      }
      named_bar(1 + c.wg, 128);
      if (c.tid == 0) { mbar_arrive_both(empty1 + 8 * 5); mbar_arrive_both(empty1 + 8 * 6); }
    }
    if (c.wg == 0 && c.tid == 0) TS(1);
    unsigned* myflag = &g_flags[m * 8 + role];
    {
      uint32_t it = 0;
      const int nt = num_tiles(j);
#pragma unroll 1
      for (int t = 0; t < nt; ++t) {
        Tile T = get_tile(p, j, t);
        if (T.nb == 4) {
          float acc[128] = {};
          g1_tile<4>(c, acc, t, areg);
          if (T.is_h) epi_h<4>(c, acc, row0, T.col); else epi_qkv<4>(c, acc, row0, T.col);
        } else if (T.nb == 3) {
          float acc[96] = {};
          g1_tile<3>(c, acc, t, areg);
          epi_qkv<3>(c, acc, row0, T.col);
        } else {
          float acc[64] = {};
          g1_tile<2>(c, acc, t, areg);
          epi_qkv<2>(c, acc, row0, T.col);
        }
        if (t == nt - 1 && c.tid == 0) {
          for (int s = 0; s < NS2; ++s) { mbar_arrive_both(empty2 + 8 * s); }
        }
        mbar_arrive_local(pub + 8 * t);
        if (t == 1) {
          if (c.wg == 0 && c.tid == 0) TS(11);
          attention(row0, role, m, c.wg * 4 + w, lane);
          mbar_arrive_local(pub + 8 * 6);
          if (c.wg == 0 && c.tid == 0) TS(12);
        }
        if (c.wg == 0 && c.tid == 0) TS(2 + t);
      }
    }
    const int nch = j ? 32 : 40;
    const uint32_t pitch = nch * 32 + 32;
    const uint32_t sacc = sbase + (c.wg * 64 + w * 16 + (lane >> 2)) * pitch + (lane & 3) * 8;
    if (j == 0) {
      float acc1[96] = {}, acc2[64] = {};
      wgmma_fence();
#pragma unroll 1
      for (int i = 0; i < nkb2; ++i) {
        uint32_t s = i % NS2, ph = (i / NS2) & 1;
        mbar_wait(full2 + 8 * s, ph, 3);
        if (c.wg == 0 && c.tid == 0) TS2(i);
        uint32_t a0 = sbase + s * ST2_BYTES + c.wg * 8192, b0 = sbase + s * ST2_BYTES + 16384;
        wgmma_fence();
#pragma unroll
        for (int k = 0; k < 4; ++k) {
          uint64_t da = make_desc(a0 + k * 32, 16, 1024);
          const uint32_t bk = b0 + (k >> 1) * (5 * 4096) + (k & 1) * 2048;
          wgmma_n192(acc1, da, make_desc(bk, 4096, 1024), (i | k) != 0);
          wgmma_n128(acc2, da, make_desc(bk + 3 * 4096, 4096, 1024), (i | k) != 0);
        }
        wgmma_commit();
        if (i > 0) {
          wgmma_wait<1>();
          if (c.tid < 2 && i - 1 + NS2 < nkb2) mbar_arrive_cluster(empty2 + 8 * ((i - 1) % NS2), c.tid);
        }
      }
      wgmma_wait<0>();
      if (c.wg == 0 && c.tid == 0) TS(8);
      named_bar(3, 256);
      acc_to_smem<96>(acc1, sacc, pitch);
      acc_to_smem<64>(acc2, sacc + 768, pitch);
    } else {
      float acc[128] = {};
      wgmma_fence();
#pragma unroll 1
      for (int i = 0; i < nkb2; ++i) {
        uint32_t s = i % NS2, ph = (i / NS2) & 1;
        mbar_wait(full2 + 8 * s, ph, 3);
        if (c.wg == 0 && c.tid == 0) TS2(i);
        uint32_t a0 = sbase + s * ST2_BYTES + c.wg * 8192, b0 = sbase + s * ST2_BYTES + 16384;
        wgmma_fence();
#pragma unroll
        for (int k = 0; k < 4; ++k)
          wgmma_n256(acc, make_desc(a0 + k * 32, 16, 1024), make_desc(b0 + (k >> 1) * (4 * 4096) + (k & 1) * 2048, 4096, 1024), (i | k) != 0);
        wgmma_commit();
        if (i > 0) {
          wgmma_wait<1>();
          if (c.tid < 2 && i - 1 + NS2 < nkb2) mbar_arrive_cluster(empty2 + 8 * ((i - 1) % NS2), c.tid);
        }
      }
      wgmma_wait<0>();
      if (c.wg == 0 && c.tid == 0) TS(8);
      named_bar(3, 256);
      acc_to_smem<128>(acc, sacc, pitch);
    }
    named_bar(3, 256);
    if (c.wg == 0 && c.tid == 0) TS2(60);
    {
      const int t256 = c.wg * 128 + c.tid;
      uint4* xs = g_xch + (size_t)((m * 2 + j) * 4) * 128 * 40;
      unsigned* pf = &g_flags[144 + (m * 2 + j) * 4];
#pragma unroll 3
      for (int e = t256; e < 96 * nch; e += 256) {
        int r = e / nch, cI = e - r * nch;
        r += (r >= 32 * p) ? 32 : 0;
        float4 u0 = lds128(sbase + r * pitch + cI * 32), u1 = lds128(sbase + r * pitch + cI * 32 + 16);
        xs[((size_t)p * 128 + r) * 40 + cI] = make_uint4(pack_bf16(u0.x, u0.y), pack_bf16(u0.z, u0.w), pack_bf16(u1.x, u1.y), pack_bf16(u1.z, u1.w));
      }
      __threadfence();
      __syncwarp();
      if (lane < 4 && lane != p) flag_add(pf + lane);
      warp_flag_wait(pf + p, 24);
      if (c.wg == 0 && c.tid == 0) TS(9);
      const int nit = nch >> 3;
#pragma unroll
      for (int i = 0; i < 5; ++i) {
        if (i < nit) {
          const int e = t256 + i * 256;
          const int rl = e / nch, cI = e - rl * nch, r = 32 * p + rl;
          uint4 v[3];
#pragma unroll
          for (int k = 0; k < 3; ++k) v[k] = __ldcg(xs + ((size_t)(k + (k >= p)) * 128 + r) * 40 + cI);
          const size_t off = (size_t)(row0 + r) * D_ + ncol0 + cI * 8;
          const uint4 xv = __ldg((const uint4*)(x + off));
          float4 u0 = lds128(sbase + r * pitch + cI * 32), u1 = lds128(sbase + r * pitch + cI * 32 + 16);
          float f[8] = {u0.x, u0.y, u0.z, u0.w, u1.x, u1.y, u1.z, u1.w};
          uint32_t o[4];
#pragma unroll
          for (int e2 = 0; e2 < 4; ++e2) {
            const uint32_t w0 = ((const uint32_t*)&v[0])[e2], w1 = ((const uint32_t*)&v[1])[e2], w2 = ((const uint32_t*)&v[2])[e2], w3 = ((const uint32_t*)&xv)[e2];
            float lo = f[2 * e2] + ((__uint_as_float(w0 << 16) + __uint_as_float(w1 << 16)) + (__uint_as_float(w2 << 16) + __uint_as_float(w3 << 16)));
            float hi = f[2 * e2 + 1] + ((__uint_as_float(w0 & 0xffff0000u) + __uint_as_float(w1 & 0xffff0000u)) + (__uint_as_float(w2 & 0xffff0000u) + __uint_as_float(w3 & 0xffff0000u)));
            o[e2] = pack_bf16(lo, hi);
          }
          *(uint4*)(out + off) = make_uint4(o[0], o[1], o[2], o[3]);
        }
      }
      if (c.wg == 0 && c.tid == 0) TS(10);
    }
    named_bar(1 + c.wg, 128);
    if (c.tid == 0) agent_exit();
  }
}

typedef CUresult (*EncodeFn)(CUtensorMap*, CUtensorMapDataType, cuuint32_t, void*, const cuuint64_t*, const cuuint64_t*,
                             const cuuint32_t*, const cuuint32_t*, CUtensorMapInterleave, CUtensorMapSwizzle,
                             CUtensorMapL2promotion, CUtensorMapFloatOOBfill);

static void make_map2(EncodeFn enc, CUtensorMap* mp, const void* ptr, int rows, int cols, int box_rows) {
  cuuint64_t dims[2] = {(cuuint64_t)cols, (cuuint64_t)rows};
  cuuint64_t strides[1] = {(cuuint64_t)cols * 2};
  cuuint32_t box[2] = {64, (cuuint32_t)box_rows};
  cuuint32_t es[2] = {1, 1};
  enc(mp, CU_TENSOR_MAP_DATA_TYPE_BFLOAT16, 2, (void*)ptr, dims, strides, box, es, CU_TENSOR_MAP_INTERLEAVE_NONE,
      CU_TENSOR_MAP_SWIZZLE_128B, CU_TENSOR_MAP_L2_PROMOTION_L2_256B, CU_TENSOR_MAP_FLOAT_OOB_FILL_NONE);
}
static void make_map3(EncodeFn enc, CUtensorMap* mp, const void* ptr, int rows, int cols, int nblk) {
  cuuint64_t dims[3] = {64, (cuuint64_t)rows, (cuuint64_t)(cols / 64)};
  cuuint64_t strides[2] = {(cuuint64_t)cols * 2, 128};
  cuuint32_t box[3] = {64, 32, (cuuint32_t)nblk};
  cuuint32_t es[3] = {1, 1, 1};
  enc(mp, CU_TENSOR_MAP_DATA_TYPE_BFLOAT16, 3, (void*)ptr, dims, strides, box, es, CU_TENSOR_MAP_INTERLEAVE_NONE,
      CU_TENSOR_MAP_SWIZZLE_128B, CU_TENSOR_MAP_L2_PROMOTION_L2_256B, CU_TENSOR_MAP_FLOAT_OOB_FILL_NONE);
}

extern "C" void kernel_launch(void* const* d_in, const int* in_sizes, int n_in, void* d_out, int out_size) {
  static EncodeFn enc = nullptr;
  static void* act_ptr = nullptr;
  if (!enc) {
    void* fn = nullptr;
    cudaDriverEntryPointQueryResult qr;
    cudaGetDriverEntryPoint("cuTensorMapEncodeTiled", &fn, cudaEnableDefault, &qr);
    enc = (EncodeFn)fn;
    cudaGetSymbolAddress(&act_ptr, g_act);
    cudaFuncSetAttribute(fused_kernel, cudaFuncAttributeMaxDynamicSharedMemorySize, SMEM_BYTES);
  }
  const __nv_bfloat16* x = (const __nv_bfloat16*)d_in[0];
  CUtensorMap m_qkv1, m_qkv2, m_gate2, m_up2, m_wo5, m_wo4, m_down5, m_down4, m_act;
  make_map3(enc, &m_qkv1, d_in[1], D_, QKV_, 1);
  make_map3(enc, &m_qkv2, d_in[1], D_, QKV_, 2);
  make_map3(enc, &m_gate2, d_in[4], D_, F_, 2);
  make_map3(enc, &m_up2, d_in[5], D_, F_, 2);
  make_map3(enc, &m_wo5, d_in[2], D_, D_, 5);
  make_map3(enc, &m_wo4, d_in[2], D_, D_, 4);
  make_map3(enc, &m_down5, d_in[6], F_, D_, 5);
  make_map3(enc, &m_down4, d_in[6], F_, D_, 4);
  make_map2(enc, &m_act, act_ptr, S_, ACT_, 128);
  fused_kernel<<<128, 384, SMEM_BYTES>>>(m_qkv1, m_qkv2, m_gate2, m_up2, m_wo5, m_wo4, m_down5, m_down4, m_act, x, (__nv_bfloat16*)d_out);
}
```
